```python
import torch

def _softmax(x, axis=-1):
    return torch.softmax(x, dim=axis)
def _gelu(x):
    return torch.nn.functional.gelu(x, approximate="tanh")
def _silu(x):
    return torch.nn.functional.silu(x)
def _sigmoid(x):
    return torch.sigmoid(x)
def _layernorm(x, axis=-1, eps=1e-5):
    m = x.mean(dim=axis, keepdim=True)
    v = x.var(dim=axis, keepdim=True, unbiased=False)
    return (x - m) / torch.sqrt(v + eps)
def _scatter_add(tgt, idx, src, axis=0):
    return tgt.clone().index_add_(axis, idx, src)
def _segment_sum(src, seg, n):
    out = torch.zeros((n,) + src.shape[1:], dtype=src.dtype)
    return out.index_add_(0, seg, src)
def _pad(x, pw):
    flat = tuple(v for pair in reversed(pw) for v in pair)
    return torch.nn.functional.pad(x, flat)

kernel_name = 'gated_mix__softmax_full_mha__sliding_block__prompt'

def setup_inputs():

    _w = (lambda a: (lambda t: t.to(torch.bfloat16) if t.is_floating_point() else t)(torch.as_tensor(a)))
    def _A_setup():
        B, S, D = 1, 2048, 512
        return {
            "x": _w((lambda *s: torch.randn(*s, dtype=torch.bfloat16) * 0.05)(B, S, D)),
            "wqkv": _w((lambda *s: torch.randn(*s, dtype=torch.bfloat16) * 1.6)(D, 3 * D)),
            "wo": _w((lambda *s: torch.randn(*s, dtype=torch.bfloat16) * 0.1)(D, D)),
        }
    _A_in = _A_setup()

    def _B_setup():
        B, S, D = 1, 2048, 512
        return {
            "x": _w((lambda *s: torch.randn(*s, dtype=torch.bfloat16) * 0.05)(B, S, D)),
            "wqkv": _w((lambda *s: torch.randn(*s, dtype=torch.bfloat16) * 1.6)(D, 3 * D)),
            "wo": _w((lambda *s: torch.randn(*s, dtype=torch.bfloat16) * 0.05)(D, D)),
        }
    _B_in = _B_setup()

    return {
        "A_x": _A_in["x"],
        "A_wqkv": _A_in["wqkv"],
        "A_wo": _A_in["wo"],
        "B_x": _B_in["x"],
        "B_wqkv": _B_in["wqkv"],
        "B_wo": _B_in["wo"],
        "gate_w": _w((lambda *s: torch.randn(*s, dtype=torch.bfloat16) * 0.05)(512) * 16.0),
    }

def reference(A_x, A_wqkv, A_wo, B_x, B_wqkv, B_wo, gate_w):
    def _A_ref(x, wqkv, wo):
        B, S, D = x.shape
        H = 32; Dh = D // H
        qkv = (lambda x, *d: x.permute(*d))((x @ wqkv).reshape(B, S, 3, H, Dh), 2, 0, 3, 1, 4)
        q, k, v = qkv[0], qkv[1], qkv[2]
        scale = Dh ** -0.5
        scores = torch.einsum("bhqd,bhkd->bhqk", q, k) * scale
        p = _softmax(scores, axis=-1)
        o = torch.einsum("bhqk,bhkd->bhqd", p, v)
        return (lambda x, *d: x.permute(*d))(o, 0, 2, 1, 3).reshape(B, S, D) @ wo

    def _B_ref(x, wqkv, wo):
        B, S, D = x.shape
        H = 32; Dh = D // H; W = 256
        qkv = (lambda x, *d: x.permute(*d))((x @ wqkv).reshape(B, S, 3, H, Dh), 2, 0, 3, 1, 4)
        q, k, v = qkv[0], qkv[1], qkv[2]
        scores = torch.einsum("bhqd,bhkd->bhqk", q, k) * (Dh ** -0.5)
        idx = torch.arange(S)
        mask = (idx[:, None] - idx[None, :] >= 0) & (idx[:, None] - idx[None, :] < W)
        scores = torch.where(mask[None, None], scores, -1e9)
        p = _softmax(scores, axis=-1)
        o = torch.einsum("bhqk,bhkd->bhqd", p, v)
        return (lambda x, *d: x.permute(*d))(o, 0, 2, 1, 3).reshape(B, S, D) @ wo

    x = A_x
    g = _sigmoid((x * gate_w).sum(-1, keepdims=True))
    a = _A_ref(x, A_wqkv, A_wo)
    b = _B_ref(x, B_wqkv, B_wo)
    return g * a + (1 - g) * b
```

```cpp
#include <cuda_runtime.h>
#include <cuda_bf16.h>
#include <cuda.h>
#include <stdint.h>

namespace {
constexpr int S_ = 2048, D_ = 512, H_ = 32;
constexpr float QSCALE = 0.25f * 1.4426950408889634f;

__device__ uint4 g_qkv[2][3][H_][2][S_];
__device__ float g_nrm[2][3][H_][128];
__device__ float g_gate[S_];
__device__ uint4 g_o[S_ / 64][64][8][2][8];

#define TS(k, i)
__device__ __forceinline__ uint32_t smem_u32(const void* p) { return (uint32_t)__cvta_generic_to_shared(p); }
__device__ __forceinline__ void mbar_init(uint32_t bar, int cnt) { asm volatile("mbarrier.init.shared::cta.b64 [%0], %1;" ::"r"(bar), "r"(cnt)); }
__device__ __forceinline__ void mbar_expect(uint32_t bar, uint32_t bytes) { asm volatile("mbarrier.arrive.expect_tx.shared::cta.b64 _, [%0], %1;" ::"r"(bar), "r"(bytes) : "memory"); }
__device__ __forceinline__ void mbar_arrive(uint32_t bar) { asm volatile("mbarrier.arrive.shared::cta.b64 _, [%0];" ::"r"(bar) : "memory"); }
__device__ __forceinline__ void mbar_arrive_cluster(uint32_t bar, uint32_t cta) {
  asm volatile("{\n.reg .b32 ra;\nmapa.shared::cluster.u32 ra, %0, %1;\nmbarrier.arrive.shared::cluster.b64 _, [ra];\n}" ::"r"(bar), "r"(cta) : "memory");
}
__device__ __forceinline__ void mbar_wait(uint32_t bar, uint32_t parity) {
  uint32_t done = 0;
  for (int spins = 0; !done && spins < (1 << 22); spins++)
    asm volatile("{\n.reg .pred p;\nmbarrier.try_wait.parity.shared::cta.b64 p, [%1], %2;\nselp.u32 %0, 1, 0, p;\n}" : "=r"(done) : "r"(bar), "r"(parity) : "memory");
}
__device__ __forceinline__ void mbar_wait_cluster(uint32_t bar, uint32_t parity) {
  uint32_t done = 0;
  for (int spins = 0; !done && spins < (1 << 22); spins++)
    asm volatile("{\n.reg .pred p;\nmbarrier.try_wait.parity.acquire.cluster.shared::cta.b64 p, [%1], %2;\nselp.u32 %0, 1, 0, p;\n}" : "=r"(done) : "r"(bar), "r"(parity) : "memory");
}
__device__ __forceinline__ void bulk_load(uint32_t dst, const void* src, uint32_t bytes, uint32_t bar) {
  asm volatile("cp.async.bulk.shared::cluster.global.mbarrier::complete_tx::bytes [%0], [%1], %2, [%3];" ::"r"(dst), "l"(src), "r"(bytes), "r"(bar) : "memory");
}
__device__ __forceinline__ void tma_2d(uint32_t dst, const CUtensorMap* tm, int c0, int c1, uint32_t bar) {
  asm volatile("cp.async.bulk.tensor.2d.shared::cluster.global.mbarrier::complete_tx::bytes [%0], [%1, {%3, %4}], [%2];" ::"r"(dst), "l"(tm), "r"(bar), "r"(c0), "r"(c1) : "memory");
}
__device__ __forceinline__ void tma_2d_mc(uint32_t dst, const CUtensorMap* tm, int c0, int c1, uint32_t bar, uint16_t mask) {
  asm volatile("cp.async.bulk.tensor.2d.shared::cluster.global.mbarrier::complete_tx::bytes.multicast::cluster [%0], [%1, {%3, %4}], [%2], %5;" ::"r"(dst), "l"(tm), "r"(bar), "r"(c0), "r"(c1), "h"(mask) : "memory");
}
__device__ __forceinline__ void cluster_sync_relaxed() { asm volatile("barrier.cluster.arrive.relaxed.aligned;\nbarrier.cluster.wait.aligned;" ::: "memory"); }
__device__ __forceinline__ void cluster_sync() { asm volatile("barrier.cluster.arrive.aligned;\nbarrier.cluster.wait.aligned;" ::: "memory"); }
#define PDL_WAIT() asm volatile("griddepcontrol.wait;" ::: "memory")
#define PDL_LAUNCH() asm volatile("griddepcontrol.launch_dependents;" ::: "memory")
#define WG_FENCE() asm volatile("wgmma.fence.sync.aligned;" ::: "memory")
#define WG_COMMIT() asm volatile("wgmma.commit_group.sync.aligned;" ::: "memory")
#define WG_WAIT(n) asm volatile("wgmma.wait_group.sync.aligned " #n ";" ::: "memory")

template <int N> __device__ __forceinline__ void fence_regs(float (&r)[N]) {
#pragma unroll
  for (int i = 0; i < N; i++) asm volatile("" : "+f"(r[i])::"memory");
}
template <int N> __device__ __forceinline__ void fence_regs(uint32_t (&r)[N]) {
#pragma unroll
  for (int i = 0; i < N; i++) asm volatile("" : "+r"(r[i])::"memory");
}
__device__ __forceinline__ uint32_t pack_bf16(float lo, float hi) {
  uint32_t r; asm("cvt.rn.bf16x2.f32 %0, %1, %2;" : "=r"(r) : "f"(hi), "f"(lo)); return r;
}
__device__ __forceinline__ float ex2(float x) { float r; asm("ex2.approx.ftz.f32 %0, %1;" : "=f"(r) : "f"(x)); return r; }
__device__ __forceinline__ uint64_t make_desc(uint32_t addr, uint32_t lbo, uint32_t sbo, uint32_t swz) {
  return (uint64_t)((addr & 0x3FFFF) >> 4) | ((uint64_t)(lbo >> 4) << 16) | ((uint64_t)(sbo >> 4) << 32) | ((uint64_t)swz << 62);
}

__device__ __forceinline__ void wgmma_n192(float (&d)[96], uint64_t da, uint64_t db, int acc) {
  asm volatile(
      "{\n.reg .pred p;\nsetp.ne.b32 p, %98, 0;\n"
      "wgmma.mma_async.sync.aligned.m64n192k16.f32.bf16.bf16 "
      "{%0,%1,%2,%3,%4,%5,%6,%7,%8,%9,%10,%11,%12,%13,%14,%15,%16,%17,%18,%19,%20,%21,%22,%23,%24,%25,%26,%27,%28,%29,%30,%31,%32,%33,%34,%35,%36,%37,%38,%39,%40,%41,%42,%43,%44,%45,%46,%47,%48,%49,%50,%51,%52,%53,%54,%55,%56,%57,%58,%59,%60,%61,%62,%63,%64,%65,%66,%67,%68,%69,%70,%71,%72,%73,%74,%75,%76,%77,%78,%79,%80,%81,%82,%83,%84,%85,%86,%87,%88,%89,%90,%91,%92,%93,%94,%95}, "
      "%96, %97, p, 1, 1, 0, 1;\n}\n"
      : "+f"(d[0]), "+f"(d[1]), "+f"(d[2]), "+f"(d[3]), "+f"(d[4]), "+f"(d[5]), "+f"(d[6]), "+f"(d[7]),
        "+f"(d[8]), "+f"(d[9]), "+f"(d[10]), "+f"(d[11]), "+f"(d[12]), "+f"(d[13]), "+f"(d[14]), "+f"(d[15]),
        "+f"(d[16]), "+f"(d[17]), "+f"(d[18]), "+f"(d[19]), "+f"(d[20]), "+f"(d[21]), "+f"(d[22]), "+f"(d[23]),
        "+f"(d[24]), "+f"(d[25]), "+f"(d[26]), "+f"(d[27]), "+f"(d[28]), "+f"(d[29]), "+f"(d[30]), "+f"(d[31]),
        "+f"(d[32]), "+f"(d[33]), "+f"(d[34]), "+f"(d[35]), "+f"(d[36]), "+f"(d[37]), "+f"(d[38]), "+f"(d[39]),
        "+f"(d[40]), "+f"(d[41]), "+f"(d[42]), "+f"(d[43]), "+f"(d[44]), "+f"(d[45]), "+f"(d[46]), "+f"(d[47]),
        "+f"(d[48]), "+f"(d[49]), "+f"(d[50]), "+f"(d[51]), "+f"(d[52]), "+f"(d[53]), "+f"(d[54]), "+f"(d[55]),
        "+f"(d[56]), "+f"(d[57]), "+f"(d[58]), "+f"(d[59]), "+f"(d[60]), "+f"(d[61]), "+f"(d[62]), "+f"(d[63]),
        "+f"(d[64]), "+f"(d[65]), "+f"(d[66]), "+f"(d[67]), "+f"(d[68]), "+f"(d[69]), "+f"(d[70]), "+f"(d[71]),
        "+f"(d[72]), "+f"(d[73]), "+f"(d[74]), "+f"(d[75]), "+f"(d[76]), "+f"(d[77]), "+f"(d[78]), "+f"(d[79]),
        "+f"(d[80]), "+f"(d[81]), "+f"(d[82]), "+f"(d[83]), "+f"(d[84]), "+f"(d[85]), "+f"(d[86]), "+f"(d[87]),
        "+f"(d[88]), "+f"(d[89]), "+f"(d[90]), "+f"(d[91]), "+f"(d[92]), "+f"(d[93]), "+f"(d[94]), "+f"(d[95])
      : "l"(da), "l"(db), "r"(acc));
}

__device__ __forceinline__ void wgmma_n128(float (&d)[64], uint64_t da, uint64_t db, int acc) {
  asm volatile(
      "{\n.reg .pred p;\nsetp.ne.b32 p, %66, 0;\n"
      "wgmma.mma_async.sync.aligned.m64n128k16.f32.bf16.bf16 "
      "{%0,%1,%2,%3,%4,%5,%6,%7,%8,%9,%10,%11,%12,%13,%14,%15,%16,%17,%18,%19,%20,%21,%22,%23,%24,%25,%26,%27,%28,%29,%30,%31,%32,%33,%34,%35,%36,%37,%38,%39,%40,%41,%42,%43,%44,%45,%46,%47,%48,%49,%50,%51,%52,%53,%54,%55,%56,%57,%58,%59,%60,%61,%62,%63}, "
      "%64, %65, p, 1, 1, 0, 1;\n}\n"
      : "+f"(d[0]), "+f"(d[1]), "+f"(d[2]), "+f"(d[3]), "+f"(d[4]), "+f"(d[5]), "+f"(d[6]), "+f"(d[7]),
        "+f"(d[8]), "+f"(d[9]), "+f"(d[10]), "+f"(d[11]), "+f"(d[12]), "+f"(d[13]), "+f"(d[14]), "+f"(d[15]),
        "+f"(d[16]), "+f"(d[17]), "+f"(d[18]), "+f"(d[19]), "+f"(d[20]), "+f"(d[21]), "+f"(d[22]), "+f"(d[23]),
        "+f"(d[24]), "+f"(d[25]), "+f"(d[26]), "+f"(d[27]), "+f"(d[28]), "+f"(d[29]), "+f"(d[30]), "+f"(d[31]),
        "+f"(d[32]), "+f"(d[33]), "+f"(d[34]), "+f"(d[35]), "+f"(d[36]), "+f"(d[37]), "+f"(d[38]), "+f"(d[39]),
        "+f"(d[40]), "+f"(d[41]), "+f"(d[42]), "+f"(d[43]), "+f"(d[44]), "+f"(d[45]), "+f"(d[46]), "+f"(d[47]),
        "+f"(d[48]), "+f"(d[49]), "+f"(d[50]), "+f"(d[51]), "+f"(d[52]), "+f"(d[53]), "+f"(d[54]), "+f"(d[55]),
        "+f"(d[56]), "+f"(d[57]), "+f"(d[58]), "+f"(d[59]), "+f"(d[60]), "+f"(d[61]), "+f"(d[62]), "+f"(d[63])
      : "l"(da), "l"(db), "r"(acc));
}

constexpr int K1_NST = 6, K1_W = 131072, K1_BAR = K1_W + K1_NST * 16384;
constexpr int K1_SMEM = K1_BAR + 256 + 1024;

__device__ __forceinline__ void k1_store_group(const float (&acc)[64], int j, float sc, uint32_t* dst, int& nm, int lane) {
  float v[8];
#pragma unroll
  for (int e = 0; e < 8; e++) v[e] = acc[8 * j + e] * sc;
  const uint32_t a0 = pack_bf16(v[0], v[1]), a1 = pack_bf16(v[2], v[3]), a2 = pack_bf16(v[4], v[5]), a3 = pack_bf16(v[6], v[7]);
  uint32_t* p = dst + j * (8 * S_);
  p[0] = a0; p[32] = a1; p[4 * S_] = a2; p[4 * S_ + 32] = a3;
  const float s0 = fmaf(v[0], v[0], fmaf(v[1], v[1], fmaf(v[4], v[4], v[5] * v[5])));
  const float s1 = fmaf(v[2], v[2], fmaf(v[3], v[3], fmaf(v[6], v[6], v[7] * v[7])));
  float t = ((lane & 1) ? s1 : s0) + __shfl_xor_sync(0xffffffff, (lane & 1) ? s0 : s1, 1);
  t += __shfl_xor_sync(0xffffffff, t, 2);
  int m = __float_as_int(t);
  m = __reduce_max_sync(0xffffffff, m);
  nm = lane == j ? m : nm;
}

__global__ void __cluster_dims__(2, 1, 1) __launch_bounds__(320, 1)
qkv_kernel(const __grid_constant__ CUtensorMap tm_x, const __grid_constant__ CUtensorMap tm_wa, const __grid_constant__ CUtensorMap tm_wb,
           const __nv_bfloat16* __restrict__ gw) {
  extern __shared__ uint8_t smem_raw[];
  const uint32_t sb = (smem_u32(smem_raw) + 1023) & ~1023u;
  const uint32_t bar_full = sb + K1_BAR, bar_empty = bar_full + 64, bar_x = bar_full + 128;
  const int tid = threadIdx.x, lane = tid & 31;
  const int wid = __shfl_sync(0xffffffff, tid >> 5, 0);
  const int rank = blockIdx.x & 1;
  const int mblk = blockIdx.x & 15, nt = blockIdx.x >> 4;
  if (wid == 8) {
    if (lane == 0) {
      TS(0, 0);
      for (int i = 0; i < K1_NST; i++) { mbar_init(bar_full + 8 * i, 1); mbar_init(bar_empty + 8 * i, 4); }
      for (int i = 0; i < 8; i++) mbar_init(bar_x + 8 * i, 1);
      asm volatile("fence.mbarrier_init.release.cluster;" ::: "memory");
      asm volatile("prefetch.tensormap [%0];" ::"l"(&tm_wa) : "memory");
      for (int kb = 0; kb < 2; kb++) { mbar_expect(bar_x + 8 * kb, 16384); tma_2d(sb + kb * 16384, &tm_x, kb * 64, mblk * 128, bar_x + 8 * kb); }
    }
    __syncwarp();
  }
  PDL_LAUNCH();
  cluster_sync_relaxed();
  if (wid == 8) {
    if (lane == 0) {
      TS(0, 1);
#pragma unroll 1
      for (int it = 0; it < 24; it++) {
        const int s = it % K1_NST, sub = nt + (it >> 3) * 8, kb = it & 7;
        if (it >= K1_NST) mbar_wait(bar_empty + 8 * s, (it / K1_NST - 1) & 1);
        mbar_expect(bar_full + 8 * s, 16384);
        tma_2d_mc(sb + K1_W + s * 16384 + rank * 8192, sub >= 12 ? &tm_wb : &tm_wa, (sub >= 12 ? sub - 12 : sub) * 128 + rank * 64, kb * 64,
                  bar_full + 8 * s, 3);
        if (it < 6) { mbar_expect(bar_x + 8 * (it + 2), 16384); tma_2d(sb + (it + 2) * 16384, &tm_x, (it + 2) * 64, mblk * 128, bar_x + 8 * (it + 2)); }
      }
    }
  } else if (wid == 9) {
    uint4 w0 = reinterpret_cast<const uint4*>(gw)[lane], w1 = reinterpret_cast<const uint4*>(gw)[lane + 32];
    const uint32_t wv[8] = {w0.x, w0.y, w0.z, w0.w, w1.x, w1.y, w1.z, w1.w};
    for (int i = 0; i < 8; i++) mbar_wait(bar_x + 8 * i, 0);
    float sum[16];
#pragma unroll
    for (int i = 0; i < 16; i++) {
      const uint32_t xa = sb + (lane >> 3) * 16384 + (nt * 16 + i) * 128 + (((lane ^ i) & 7) << 4);
      uint4 a0, a1;
      asm volatile("ld.shared.v4.u32 {%0,%1,%2,%3}, [%4];" : "=r"(a0.x), "=r"(a0.y), "=r"(a0.z), "=r"(a0.w) : "r"(xa));
      asm volatile("ld.shared.v4.u32 {%0,%1,%2,%3}, [%4];" : "=r"(a1.x), "=r"(a1.y), "=r"(a1.z), "=r"(a1.w) : "r"(xa + 65536));
      const uint32_t av[8] = {a0.x, a0.y, a0.z, a0.w, a1.x, a1.y, a1.z, a1.w};
      float s = 0.f;
#pragma unroll
      for (int j = 0; j < 8; j++) {
        s = fmaf(__uint_as_float(av[j] << 16), __uint_as_float(wv[j] << 16), s);
        s = fmaf(__uint_as_float(av[j] & 0xFFFF0000u), __uint_as_float(wv[j] & 0xFFFF0000u), s);
      }
      sum[i] = s;
    }
#pragma unroll
    for (int o = 8; o; o >>= 1) {
#pragma unroll
      for (int i = 0; i < o; i++) {
        const bool up = lane & o;
        sum[i] = (up ? sum[i + o] : sum[i]) + __shfl_xor_sync(0xffffffff, up ? sum[i] : sum[i + o], o);
      }
    }
    sum[0] += __shfl_xor_sync(0xffffffff, sum[0], 16);
    if (lane < 16) g_gate[mblk * 128 + nt * 16 + lane] = 1.0f / (1.0f + __expf(-sum[0]));
    if (lane == 0) TS(0, 6);
  } else {
    const int wg = wid >> 2;
    const int row0 = mblk * 128 + wid * 16;
    float accA[64], accB[64];
    const uint64_t da = make_desc(sb + wg * 8192, 16, 1024, 1);
    const uint64_t db = make_desc(sb + K1_W, 8192, 1024, 1);
    uint32_t* dst = reinterpret_cast<uint32_t*>(&g_qkv[0][0][0][0][0] + (size_t)nt * 8 * 2 * S_ + row0) + lane;
    float* ndst = &g_nrm[0][0][0][0] + (nt * 8 + lane) * 128 + (row0 >> 4);
#define K1_MMA(acc, it)                                                                            \
    {                                                                                               \
      mbar_wait(bar_full + 8 * ((it) % K1_NST), ((it) / K1_NST) & 1);                               \
      WG_FENCE();                                                                                   \
      _Pragma("unroll") for (int k = 0; k < 4; k++)                                                 \
        wgmma_n128(acc, da + ((it) & 7) * 1024 + k * 2, db + ((it) % K1_NST) * 1024 + k * 128, (((it) & 7) | k) != 0); \
      WG_COMMIT();                                                                                  \
      if ((it) > 0) WG_WAIT(1);                                                                     \
      if ((it) > 0 && (it) <= 24 - K1_NST && (tid & 127) < 2) mbar_arrive_cluster(bar_empty + 8 * (((it) - 1) % K1_NST), tid & 1); \
    }
#pragma unroll
    for (int kb = 0; kb < 8; kb++) {
      mbar_wait(bar_x + 8 * kb, 0);
      if (tid == 0) TS(0, 8 + kb);
      K1_MMA(accA, kb);
    }
    int nm = 0;
    if (tid == 0) TS(0, 2);
#pragma unroll
    for (int kb = 0; kb < 8; kb++) {
      K1_MMA(accB, 8 + kb);
      if (kb == 0) fence_regs(accA);
      k1_store_group(accA, kb, nt < 4 ? QSCALE : 1.0f, dst, nm, lane);
    }
    if (lane < 8) ndst[0] = __int_as_float(nm);
    if (tid == 0) TS(0, 5);
#pragma unroll
    for (int kb = 0; kb < 8; kb++) {
      K1_MMA(accA, 16 + kb);
      if (kb == 0) fence_regs(accB);
      k1_store_group(accB, kb, nt >= 4 ? QSCALE : 1.0f, dst + 64 * 8 * S_, nm, lane);
    }
    if (lane < 8) ndst[64 * 128] = __int_as_float(nm);
    WG_WAIT(0);
    fence_regs(accA);
    if (tid == 0) TS(0, 3);
#pragma unroll
    for (int kb = 0; kb < 8; kb++) k1_store_group(accA, kb, 1.0f, dst + 128 * 8 * S_, nm, lane);
    if (lane < 8) ndst[128 * 128] = __int_as_float(nm);
    if (tid == 0) TS(0, 4);
#undef K1_MMA
  }
}

__device__ __forceinline__ void wgmma_s64(float (&d)[32], const uint32_t (&a)[4], uint64_t desc) {
  asm volatile(
      "wgmma.mma_async.sync.aligned.m64n64k16.f32.bf16.bf16 "
      "{%0,%1,%2,%3,%4,%5,%6,%7,%8,%9,%10,%11,%12,%13,%14,%15,%16,%17,%18,%19,%20,%21,%22,%23,%24,%25,%26,%27,%28,%29,%30,%31}, "
      "{%32,%33,%34,%35}, %36, 0, 1, 1, 0;\n"
      : "+f"(d[0]), "+f"(d[1]), "+f"(d[2]), "+f"(d[3]), "+f"(d[4]), "+f"(d[5]), "+f"(d[6]), "+f"(d[7]),
        "+f"(d[8]), "+f"(d[9]), "+f"(d[10]), "+f"(d[11]), "+f"(d[12]), "+f"(d[13]), "+f"(d[14]), "+f"(d[15]),
        "+f"(d[16]), "+f"(d[17]), "+f"(d[18]), "+f"(d[19]), "+f"(d[20]), "+f"(d[21]), "+f"(d[22]), "+f"(d[23]),
        "+f"(d[24]), "+f"(d[25]), "+f"(d[26]), "+f"(d[27]), "+f"(d[28]), "+f"(d[29]), "+f"(d[30]), "+f"(d[31])
      : "r"(a[0]), "r"(a[1]), "r"(a[2]), "r"(a[3]), "l"(desc));
}
__device__ __forceinline__ void wgmma_pv(float (&o)[12], uint32_t a0, uint32_t a1, uint32_t a2, uint32_t a3, uint64_t desc) {
  asm volatile(
      "wgmma.mma_async.sync.aligned.m64n24k16.f32.bf16.bf16 "
      "{%0,%1,%2,%3,%4,%5,%6,%7,%8,%9,%10,%11}, {%12,%13,%14,%15}, %16, 1, 1, 1, 1;\n"
      : "+f"(o[0]), "+f"(o[1]), "+f"(o[2]), "+f"(o[3]), "+f"(o[4]), "+f"(o[5]), "+f"(o[6]), "+f"(o[7]), "+f"(o[8]), "+f"(o[9]), "+f"(o[10]), "+f"(o[11])
      : "r"(a0), "r"(a1), "r"(a2), "r"(a3), "l"(desc));
}
__device__ __forceinline__ void issue_pv(float (&o)[12], const uint32_t (&p)[16], uint64_t dv) {
#pragma unroll
  for (int i = 0; i < 4; i++) wgmma_pv(o, p[4 * i], p[4 * i + 1], p[4 * i + 2], p[4 * i + 3], dv + i * 16);
}

#define MUFU_MASK 0x9249
#define PACK_PRMT 0
#define NWG 4
#define USE_PDL 1
__device__ __forceinline__ uint32_t exp_fma_pair(float x0, float x1, uint32_t cu) {
  const float M0 = 65536.0f + 127.0f - 1.59375f, M1 = 66032.0f - 1.59375f;
  uint32_t t0 = __float_as_uint(x0 + M0), t1 = __float_as_uint(x1 + M1);
  uint32_t w = t1 * 65536u + t0;
  uint32_t u, d;
  asm("lop3.b32 %0, %1, 0x007F007F, %2, 0xEA;" : "=r"(u) : "r"(w), "r"(cu));
  asm("fma.rn.bf16x2 %0, %1, %1, %2;" : "=r"(d) : "r"(u), "r"(0x40014001u));
  return d + w - u;
}
__device__ __forceinline__ void exp_tile(const float (&s)[32], uint32_t (&p)[16], uint32_t cu) {
#pragma unroll
  for (int m = 0; m < 16; m++) {
    if ((MUFU_MASK >> m) & 1) p[m] = pack_bf16(ex2(s[2 * m]), ex2(s[2 * m + 1]));
    else p[m] = exp_fma_pair(s[2 * m], s[2 * m + 1], cu);
  }
}
__device__ __forceinline__ void mask_tile(uint32_t (&p)[16], int dbase, int mode) {
  int sh0 = 16 - 16 * dbase;
  asm volatile("" : "+r"(sh0));
#pragma unroll
  for (int m = 0; m < 16; m++) {
    uint32_t keep;
    asm("shr.u32 %0, %1, %2;" : "=r"(keep) : "r"(0xFFFFFFFFu), "r"(max(sh0 - 128 * (m & 1) + 128 * (m >> 1), 0)));
    p[m] &= mode == 1 ? ~keep : keep;
  }
}

constexpr int SM_KA = 0;
constexpr int SM_KB = 65536;
constexpr int SM_VBLO = SM_KB + 24576;
constexpr int SM_ONE = SM_VBLO + 12288 + 32768;
constexpr int SM_VAHI = SM_ONE + 12288;
constexpr int SM_VBHI = SM_VAHI + 32768;
constexpr int SM_BAR = SM_VBHI + 12288;
constexpr int SM_TOTAL = SM_BAR + 128;

__device__ __forceinline__ void load_q(uint32_t (&q)[4], int br, int h, int row0, int warp, int lane) {
  const uint32_t* p = reinterpret_cast<const uint32_t*>(&g_qkv[br][0][h][0][row0 + warp * 16]) + lane;
  q[0] = p[0]; q[1] = p[32]; q[2] = p[4 * S_]; q[3] = p[4 * S_ + 32];
}
__device__ __forceinline__ void store_o(const float (&o)[12], float g0, float g1, int br, int h, int row0, int warp, int lane) {
  if (br) { g0 = 1.0f - g0; g1 = 1.0f - g1; }
  const float s0 = __fdividef(g0, o[4]), s1 = __fdividef(g1, o[6]);
  uint32_t* dst = reinterpret_cast<uint32_t*>(&g_o[row0 >> 6][br * 32 + h][warp * 2][0][0]) + lane;
  dst[0] = pack_bf16(o[0] * s0, o[1] * s0);
  dst[64] = pack_bf16(o[2] * s1, o[3] * s1);
  dst[32] = pack_bf16(o[8] * s0, o[9] * s0);
  dst[96] = pack_bf16(o[10] * s1, o[11] * s1);
}
__device__ __forceinline__ bool range_ok(int br, int h, int qb, int lane) {
  const int qn = __float_as_int(g_nrm[br][0][h][qb * 32 + lane]);
  const int4 k4 = reinterpret_cast<const int4*>(g_nrm[br][1][h])[lane], v4 = reinterpret_cast<const int4*>(g_nrm[br][2][h])[lane];
  const int kn = max(max(k4.x, k4.y), max(k4.z, k4.w)), vn = max(max(v4.x, v4.y), max(v4.z, v4.w));
  float q2 = __int_as_float(__reduce_max_sync(0xffffffff, qn));
  float k2 = __int_as_float(__reduce_max_sync(0xffffffff, kn));
  float v2 = __int_as_float(__reduce_max_sync(0xffffffff, vn));
  return (q2 * k2 <= 8100.0f) & (v2 <= 1.0e12f) & (v2 >= 6.0e-8f);
}
__device__ __forceinline__ void hmma(float* d, const uint32_t* a, uint32_t b0, uint32_t b1) {
  asm("mma.sync.aligned.m16n8k16.row.col.f32.bf16.bf16.f32 {%0,%1,%2,%3}, {%4,%5,%6,%7}, {%8,%9}, {%0,%1,%2,%3};"
      : "+f"(d[0]), "+f"(d[1]), "+f"(d[2]), "+f"(d[3]) : "r"(a[0]), "r"(a[1]), "r"(a[2]), "r"(a[3]), "r"(b0), "r"(b1));
}
__device__ __forceinline__ void safe_chunk(float (&o)[12], float& m0, float& m1, const uint32_t (&q)[4], uint32_t klo, uint32_t khi, uint32_t vlo, uint32_t vhi,
                                           int lane, int dbase, int mode) {
  const float ninf = __int_as_float(0xFF800000);
  asm volatile("" : "+r"(dbase));
  float t[32];
  uint32_t p[16];
#pragma unroll
  for (int j = 0; j < 8; j++) {
    uint32_t b0, b1;
    asm volatile("ld.shared.u32 %0, [%1];" : "=r"(b0) : "r"(klo + j * 128 + lane * 4));
    asm volatile("ld.shared.u32 %0, [%1];" : "=r"(b1) : "r"(khi + j * 128 + lane * 4));
    t[4 * j] = t[4 * j + 1] = t[4 * j + 2] = t[4 * j + 3] = 0.f;
    hmma(t + 4 * j, q, b0, b1);
  }
  float x0 = m0, x1 = m1;
#pragma unroll
  for (int i = 0; i < 32; i++) {
    int d = dbase + 8 * ((i >> 1) & 1) - 8 * (i >> 2) - (i & 1);
    bool keep = mode == 0 || (mode == 1 ? d < 0 : d >= 0);
    t[i] = keep ? t[i] : ninf;
    if ((i >> 1) & 1) x1 = fmaxf(x1, t[i]); else x0 = fmaxf(x0, t[i]);
  }
  x0 = fmaxf(x0, __shfl_xor_sync(0xffffffff, x0, 1)); x0 = fmaxf(x0, __shfl_xor_sync(0xffffffff, x0, 2));
  x1 = fmaxf(x1, __shfl_xor_sync(0xffffffff, x1, 1)); x1 = fmaxf(x1, __shfl_xor_sync(0xffffffff, x1, 2));
  const float y0 = x0 == ninf ? 0.f : x0, y1 = x1 == ninf ? 0.f : x1;
  const float r0 = ex2(m0 - y0), r1 = ex2(m1 - y1);
  m0 = x0; m1 = x1;
#pragma unroll
  for (int i = 0; i < 12; i++) o[i] *= ((i >> 1) & 1) ? r1 : r0;
#pragma unroll
  for (int m = 0; m < 16; m++) { float y = (m & 1) ? y1 : y0; p[m] = pack_bf16(ex2(t[2 * m] - y), ex2(t[2 * m + 1] - y)); }
#pragma unroll
  for (int i = 0; i < 4; i++) {
    uint32_t v0, v1, v2, v3;
    const uint32_t addr = ((lane & 16) ? vhi : vlo) + i * 256 + (lane & 15) * 16;
    asm volatile("ldmatrix.sync.aligned.m8n8.x4.trans.shared.b16 {%0,%1,%2,%3}, [%4];" : "=r"(v0), "=r"(v1), "=r"(v2), "=r"(v3) : "r"(addr));
    hmma(o, p + 4 * i, v0, v1);
    hmma(o + 4, p + 4 * i, 0x3F803F80u, 0x3F803F80u);
    hmma(o + 8, p + 4 * i, v2, v3);
  }
}

__device__ __forceinline__ void issue_piece(int pc, uint32_t sb, int h, int qb, int warp) {
  const int kv = 1 + (warp >> 1), half = warp & 1;
  const uint32_t b = sb + SM_BAR + 8 * pc;
  int k0, n;
  uint32_t dst;
  if (pc < 4) {
    k0 = pc * 512 + ((pc && kv == 1) ? 64 : 0);
    n = pc * 512 + ((pc < 3 && kv == 1) ? 576 : 512) - k0;
    dst = kv == 1 ? SM_KA + half * 32768 + k0 * 16 : (half ? SM_VAHI + 8192 * pc : SM_ONE - 8192 * (pc + 1));
    if (warp == 0) mbar_expect(b, n * 32 + 16384);
  } else {
    const int c0 = qb == 0 ? 4 : 0;
    k0 = 512 * qb - 256 + 64 * c0;
    n = 768 - 64 * c0;
    dst = (kv == 1 ? SM_KB + half * 12288 : (half ? SM_VBHI : SM_VBLO)) + c0 * 1024;
    if (warp == 0) mbar_expect(b, n * 64);
  }
  bulk_load(sb + dst, &g_qkv[pc >> 2][kv][h][half][k0], n * 16, b);
}

__global__ void __launch_bounds__(NWG * 128, 1) attn_kernel(int opq, const uint8_t* __restrict__ woa, const uint8_t* __restrict__ wob) {
  extern __shared__ __align__(1024) uint8_t smem[];
  const uint32_t sb = smem_u32(smem);
  const int h = blockIdx.x >> 2, qb = blockIdx.x & 3;
  const int tid = threadIdx.x, lane = tid & 31;
  const int wg = __shfl_sync(0xffffffff, tid >> 7, 0), warp = (tid >> 5) & 3;
  const uint32_t bar = sb + SM_BAR;
  if (tid == 0) {
    TS(1, 0);
    for (int i = 0; i < 5; i++) mbar_init(bar + 8 * i, 1);
    asm volatile("fence.mbarrier_init.release.cluster;" ::: "memory");
  }
  {
    const uint4 ones = make_uint4(0x3F803F80u, 0x3F803F80u, 0x3F803F80u, 0x3F803F80u);
    *reinterpret_cast<uint4*>(smem + SM_ONE + tid * 16) = ones;
    if (tid < 256) *reinterpret_cast<uint4*>(smem + SM_ONE + 8192 + tid * 16) = ones;
  }
  if (qb == 0) *reinterpret_cast<uint4*>(smem + (tid < 256 ? SM_VBLO : SM_VBHI - 4096) + tid * 16) = make_uint4(0, 0, 0, 0);
  asm volatile("fence.proxy.async.shared::cta;" ::: "memory");
  if (tid == 64) {
    asm volatile("cp.async.bulk.prefetch.L2.global [%0], 4096;" ::"l"(woa + blockIdx.x * 4096) : "memory");
    asm volatile("cp.async.bulk.prefetch.L2.global [%0], 4096;" ::"l"(wob + blockIdx.x * 4096) : "memory");
  }
  PDL_LAUNCH();
  __syncthreads();
  PDL_WAIT();
  if (tid == 128) TS(1, 1);
  if (tid < 128 && lane == 0) issue_piece(0, sb, h, qb, warp);
  const int rowb = qb * 512 + wg * 128;
  const int dbase = warp * 16 + (lane >> 2) - 2 * (lane & 3);
  const int cmin = qb == 0 ? 4 : 0;
  uint32_t q[4], qn[4];
  load_q(qn, 0, h, rowb, warp, lane);
  const bool fast = range_ok(0, h, qb, lane) & range_ok(1, h, qb, lane);
  if (fast) {
    uint32_t cu;
    asm volatile("mov.b32 %0, %1;" : "=r"(cu) : "r"(opq * (PACK_PRMT ? 0xBF80BF80u : 0x3F803F80u)));
    const uint32_t order = wg == 0 ? 0x3210u : (wg == 1 ? 0x3120u : (wg == 2 ? 0x1320u : 0x2310u));
#pragma unroll 1
    for (int job = 0; job < 4; job++) {
      const int code = (order >> (4 * job)) & 3, br = code >> 1;
      const int row0 = rowb + (code & 1) * 64;
#pragma unroll
      for (int i = 0; i < 4; i++) q[i] = qn[i];
      if (job < 3) { const int cn = (order >> (4 * job + 4)) & 3; load_q(qn, cn >> 1, h, rowb + (cn & 1) * 64, warp, lane); }
      const float g0 = g_gate[row0 + warp * 16 + (lane >> 2)], g1 = g_gate[row0 + warp * 16 + (lane >> 2) + 8];
      if (br == 0) {
        float sa[32], o[12];
        uint32_t pa[16], pc[16];
#pragma unroll
        for (int i = 0; i < 32; i++) sa[i] = 0.f;
#pragma unroll
        for (int i = 0; i < 12; i++) o[i] = 0.f;
        uint64_t dk = make_desc(sb + SM_KA, 32768, 128, 0);
        mbar_wait(bar, 0);
        if (tid == 128 && job == 0) TS(1, 2);
        fence_regs(o);
        WG_FENCE();
        wgmma_s64(sa, q, dk);
        WG_COMMIT();
        WG_WAIT(0);
#pragma unroll 1
        for (int qt = 0; qt < 4; qt++) {
          mbar_wait(bar + 8 * qt, 0);
          if (job == 0 && wg == ((qt + 1) & 3) && lane == 0) issue_piece(qt + 1, sb, h, qb, warp);
          uint64_t dv = make_desc(sb + SM_ONE - 8192 * (qt + 1), 128, 8192 * (qt + 1) + 2048, 0);
#pragma unroll 1
          for (int c = 0; c < 4; c++) {
            dk += 128;
            fence_regs(sa);
            exp_tile(sa, pa, cu);
            WG_FENCE();
            wgmma_s64(sa, q, dk - 64);
            WG_COMMIT();
            issue_pv(o, pa, dv);
            WG_COMMIT();
            WG_WAIT(1);
            fence_regs(sa);
            exp_tile(sa, pc, cu);
            WG_FENCE();
            wgmma_s64(sa, q, dk);
            WG_COMMIT();
            issue_pv(o, pc, dv + 64);
            WG_COMMIT();
            WG_WAIT(1);
            dv += 128;
          }
        }
        WG_WAIT(0);
        fence_regs(o);
        store_o(o, g0, g1, 0, h, row0, warp, lane);
      } else {
        float sa[32], o[12];
        uint32_t pa[16], pc[16];
#pragma unroll
        for (int i = 0; i < 32; i++) sa[i] = 0.f;
#pragma unroll
        for (int i = 0; i < 12; i++) o[i] = 0.f;
        const int t = wg * 2 + (code & 1);
        uint64_t dk = make_desc(sb + SM_KB + t * 1024, 12288, 128, 0), dv = make_desc(sb + SM_VBLO + t * 1024, 128, SM_ONE - SM_VBLO, 0);
        mbar_wait(bar + 32, 0);
        fence_regs(o);
        WG_FENCE();
        wgmma_s64(sa, q, dk);
        WG_COMMIT();
        WG_WAIT(0);
#pragma unroll 1
        for (int c = t; c < t + 4; c += 2) {
          dk += 128;
          fence_regs(sa);
          exp_tile(sa, pa, cu);
          if (c == t) mask_tile(pa, dbase, 1);
          if (c < cmin) {
#pragma unroll
            for (int i = 0; i < 16; i++) pa[i] = 0;
          }
          WG_FENCE();
          wgmma_s64(sa, q, dk - 64);
          WG_COMMIT();
          issue_pv(o, pa, dv);
          WG_COMMIT();
          WG_WAIT(1);
          fence_regs(sa);
          exp_tile(sa, pc, cu);
          if (c + 1 < cmin) {
#pragma unroll
            for (int i = 0; i < 16; i++) pc[i] = 0;
          }
          WG_FENCE();
          wgmma_s64(sa, q, dk);
          WG_COMMIT();
          issue_pv(o, pc, dv + 64);
          WG_COMMIT();
          WG_WAIT(1);
          dv += 128;
        }
        fence_regs(sa);
        exp_tile(sa, pa, cu);
        mask_tile(pa, dbase, 2);
        WG_FENCE();
        issue_pv(o, pa, dv);
        WG_COMMIT();
        WG_WAIT(0);
        fence_regs(o);
        store_o(o, g0, g1, 1, h, row0, warp, lane);
      }
    }
  } else {
    if (lane == 0) issue_piece(wg + 1, sb, h, qb, warp);
    for (int i = 0; i < 5; i++) mbar_wait(bar + 8 * i, 0);
#pragma unroll 1
    for (int job = 0; job < 4; job++) {
      const int br = job >> 1, t = wg * 2 + (job & 1), row0 = rowb + (job & 1) * 64;
      load_q(q, br, h, row0, warp, lane);
      float m0 = __int_as_float(0xFF800000), m1 = m0, os[12];
#pragma unroll
      for (int i = 0; i < 12; i++) os[i] = 0.f;
      const int c0 = br ? max(t, cmin) : 0, c1 = br ? t + 5 : 32;
#pragma unroll 1
      for (int c = c0; c < c1; c++) {
        const uint32_t klo = sb + (br ? SM_KB : SM_KA) + c * 1024;
        const uint32_t vlo = sb + (br ? SM_VBLO + c * 1024 : SM_ONE - 8192 * ((c >> 3) + 1) + (c & 7) * 1024);
        safe_chunk(os, m0, m1, q, klo, klo + (br ? 12288 : 32768), vlo, sb + (br ? SM_VBHI : SM_VAHI) + c * 1024, lane, dbase,
                   br ? (c == t ? 1 : (c == t + 4 ? 2 : 0)) : 0);
      }
      store_o(os, g_gate[row0 + warp * 16 + (lane >> 2)], g_gate[row0 + warp * 16 + (lane >> 2) + 8], br, h, row0, warp, lane);
    }
  }
}

constexpr int K3_W = 0, K3_A = 131072, K3_X = K3_A + 65536, K3_BAR = K3_X + 32768;
constexpr int K3_SMEM = K3_BAR + 256 + 1024;

__global__ void __cluster_dims__(2, 1, 1) __launch_bounds__(320, 1)
out_kernel(const __grid_constant__ CUtensorMap tm_wa, const __grid_constant__ CUtensorMap tm_wb, __nv_bfloat16* __restrict__ out) {
  extern __shared__ uint8_t smem_raw[];
  const uint32_t sb = (smem_u32(smem_raw) + 1023) & ~1023u;
  const uint32_t bar_w = sb + K3_BAR, bar_a = bar_w + 64, bar_e = bar_a + 32, bar_x = bar_e + 32;
  const int tid = threadIdx.x, lane = tid & 31;
  const int wid = __shfl_sync(0xffffffff, tid >> 5, 0);
  const int rank = blockIdx.x & 1, pair = blockIdx.x >> 1;
  const int nblk = pair & 3, mblk = pair >> 2;
  if (tid == 0) {
    TS(2, 0);
    for (int i = 0; i < 8; i++) { mbar_init(bar_w + 8 * i, 1); mbar_init(bar_x + 8 * i, 1); }
    for (int i = 0; i < 4; i++) { mbar_init(bar_a + 8 * i, 1); mbar_init(bar_e + 8 * i, 2); }
    for (int i = 0; i < 8; i++) mbar_expect(bar_x + 8 * i, 4096);
    asm volatile("fence.mbarrier_init.release.cluster;" ::: "memory");
  }
  __syncthreads();
  asm volatile("barrier.cluster.arrive.relaxed.aligned;" ::: "memory");
  if (wid == 8) {
    if (lane == 0) {
      const CUtensorMap* tw = rank ? &tm_wb : &tm_wa;
#pragma unroll 1
      for (int kb = 0; kb < 8; kb++) {
        if (kb >= 3) mbar_wait(bar_w + 8 * (kb - 3), 0);
        mbar_expect(bar_w + 8 * kb, 16384);
        tma_2d(sb + K3_W + kb * 16384, tw, nblk * 128, kb * 64, bar_w + 8 * kb);
        tma_2d(sb + K3_W + kb * 16384 + 8192, tw, nblk * 128 + 64, kb * 64, bar_w + 8 * kb);
      }
    }
  } else if (wid == 9) {
    if (lane == 0) {
      PDL_WAIT();
      TS(2, 1);
#pragma unroll 1
      for (int kb = 0; kb < 8; kb++) {
        const int s = kb & 3;
        if (kb >= 4) mbar_wait(bar_e + 8 * s, 0);
        mbar_expect(bar_a + 8 * s, 16384);
        bulk_load(sb + K3_A + s * 16384, &g_o[mblk * 2][rank * 32 + kb * 4][0][0][0], 8192, bar_a + 8 * s);
        bulk_load(sb + K3_A + s * 16384 + 8192, &g_o[mblk * 2 + 1][rank * 32 + kb * 4][0][0][0], 8192, bar_a + 8 * s);
      }
    }
  } else {
    const int wg = wid >> 2;
    float acc[64];
    const uint64_t da = make_desc(sb + K3_A + wg * 8192, 128, 256, 0);
    const uint64_t db = make_desc(sb + K3_W, 8192, 1024, 1);
#pragma unroll
    for (int kb = 0; kb < 8; kb++) {
      mbar_wait(bar_w + 8 * kb, 0);
      mbar_wait(bar_a + 8 * (kb & 3), kb >> 2);
      if (tid == 0 && kb == 0) TS(2, 2);
      WG_FENCE();
#pragma unroll
      for (int k = 0; k < 4; k++) wgmma_n128(acc, da + (kb & 3) * 1024 + k * 128, db + kb * 1024 + k * 128, (kb | k) != 0);
      WG_COMMIT();
      if (kb >= 1 && kb <= 4) {
        WG_WAIT(1);
        if ((tid & 127) == 0) mbar_arrive(bar_e + 8 * (kb - 1));
      }
    }
    WG_WAIT(0);
    fence_regs(acc);
    if (tid == 0) TS(2, 3);
    asm volatile("barrier.cluster.wait.aligned;" ::: "memory");
    const uint32_t wbuf = sb + K3_X + wid * 4096;
    uint32_t peer, pbar;
    asm("mapa.shared::cluster.u32 %0, %1, %2;" : "=r"(peer) : "r"(wbuf + lane * 16), "r"(rank ^ 1));
    asm("mapa.shared::cluster.u32 %0, %1, %2;" : "=r"(pbar) : "r"(bar_x + wid * 8), "r"(rank ^ 1));
#pragma unroll
    for (int i = 0; i < 8; i++) {
      float v0 = rank ? acc[4 * i] : acc[32 + 4 * i], v1 = rank ? acc[4 * i + 1] : acc[33 + 4 * i];
      float v2 = rank ? acc[4 * i + 2] : acc[34 + 4 * i], v3 = rank ? acc[4 * i + 3] : acc[35 + 4 * i];
      asm volatile("st.async.shared::cluster.mbarrier::complete_tx::bytes.v4.f32 [%0], {%1,%2,%3,%4}, [%5];" ::"r"(peer + i * 512), "f"(v0), "f"(v1),
                   "f"(v2), "f"(v3), "r"(pbar) : "memory");
    }
    mbar_wait_cluster(bar_x + wid * 8, 0);
    uint32_t pk[16];
#pragma unroll
    for (int i = 0; i < 8; i++) {
      float r0, r1, r2, r3;
      asm volatile("ld.shared.v4.f32 {%0,%1,%2,%3}, [%4];" : "=f"(r0), "=f"(r1), "=f"(r2), "=f"(r3) : "r"(wbuf + lane * 16 + i * 512));
      r0 += rank ? acc[32 + 4 * i] : acc[4 * i]; r1 += rank ? acc[33 + 4 * i] : acc[4 * i + 1];
      r2 += rank ? acc[34 + 4 * i] : acc[4 * i + 2]; r3 += rank ? acc[35 + 4 * i] : acc[4 * i + 3];
      pk[2 * i] = pack_bf16(r0, r1); pk[2 * i + 1] = pack_bf16(r2, r3);
    }
    __syncwarp();
#pragma unroll
    for (int i = 0; i < 4; i++) {
      const int r = (lane & 7) + ((lane >> 3) & 1) * 8, chunk = 2 * i + (lane >> 4);
      asm volatile("stmatrix.sync.aligned.m8n8.x4.shared.b16 [%0], {%1,%2,%3,%4};" ::"r"(wbuf + r * 128 + ((chunk ^ (r & 7)) << 4)),
                   "r"(pk[4 * i]), "r"(pk[4 * i + 1]), "r"(pk[4 * i + 2]), "r"(pk[4 * i + 3]) : "memory");
    }
    __syncwarp();
    __nv_bfloat16* op = out + (size_t)(mblk * 128 + wid * 16) * D_ + nblk * 128 + rank * 64;
#pragma unroll
    for (int i = 0; i < 4; i++) {
      const int r = i * 4 + (lane >> 3), chunk = lane & 7;
      uint4 v;
      asm volatile("ld.shared.v4.u32 {%0,%1,%2,%3}, [%4];" : "=r"(v.x), "=r"(v.y), "=r"(v.z), "=r"(v.w) : "r"(wbuf + r * 128 + ((chunk ^ (r & 7)) << 4)));
      *reinterpret_cast<uint4*>(op + r * D_ + chunk * 8) = v;
    }
    if (tid == 0) TS(2, 4);
  }
}
}

typedef CUresult (*EncodeFn)(CUtensorMap*, CUtensorMapDataType, cuuint32_t, void*, const cuuint64_t*, const cuuint64_t*, const cuuint32_t*,
                             const cuuint32_t*, CUtensorMapInterleave, CUtensorMapSwizzle, CUtensorMapL2promotion, CUtensorMapFloatOOBfill);
static void make_map(EncodeFn fn, CUtensorMap* m, const void* p, int rows, int cols, int box_rows) {
  cuuint64_t dims[2] = {(cuuint64_t)cols, (cuuint64_t)rows};
  cuuint64_t strides[1] = {(cuuint64_t)cols * 2};
  cuuint32_t box[2] = {64, (cuuint32_t)box_rows}, es[2] = {1, 1};
  fn(m, CU_TENSOR_MAP_DATA_TYPE_BFLOAT16, 2, const_cast<void*>(p), dims, strides, box, es, CU_TENSOR_MAP_INTERLEAVE_NONE,
     CU_TENSOR_MAP_SWIZZLE_128B, CU_TENSOR_MAP_L2_PROMOTION_L2_256B, CU_TENSOR_MAP_FLOAT_OOB_FILL_NONE);
}

extern "C" void kernel_launch(void* const* d_in, const int* in_sizes, int n_in, void* d_out, int out_size) {
  const __nv_bfloat16* x = (const __nv_bfloat16*)d_in[0];
  const __nv_bfloat16* gw = (const __nv_bfloat16*)d_in[6];
  void* fp = nullptr;
  cudaDriverEntryPointQueryResult qr;
  cudaGetDriverEntryPoint("cuTensorMapEncodeTiled", &fp, cudaEnableDefault, &qr);
  EncodeFn enc = (EncodeFn)fp;
  CUtensorMap tx, twa, twb, toa, tob;
  make_map(enc, &tx, x, S_, D_, 128);
  make_map(enc, &twa, d_in[1], D_, 1536, 64);
  make_map(enc, &twb, d_in[4], D_, 1536, 64);
  make_map(enc, &toa, d_in[2], D_, D_, 64);
  make_map(enc, &tob, d_in[5], D_, D_, 64);
  cudaFuncSetAttribute(qkv_kernel, cudaFuncAttributeMaxDynamicSharedMemorySize, K1_SMEM);
  cudaFuncSetAttribute(attn_kernel, cudaFuncAttributeMaxDynamicSharedMemorySize, SM_TOTAL);
  cudaFuncSetAttribute(out_kernel, cudaFuncAttributeMaxDynamicSharedMemorySize, K3_SMEM);
  cudaStream_t st = cudaStreamPerThread;
  qkv_kernel<<<128, 320, K1_SMEM, st>>>(tx, twa, twb, gw);
  cudaLaunchAttribute at[1];
  at[0].id = cudaLaunchAttributeProgrammaticStreamSerialization;
  at[0].val.programmaticStreamSerializationAllowed = 1;
  cudaLaunchConfig_t cfg = {};
  cfg.stream = st; cfg.attrs = at; cfg.numAttrs = USE_PDL;
  cfg.gridDim = dim3(128); cfg.blockDim = dim3(NWG * 128); cfg.dynamicSmemBytes = SM_TOTAL;
  cudaLaunchKernelEx(&cfg, attn_kernel, 1, (const uint8_t*)d_in[2], (const uint8_t*)d_in[5]);
  cfg.gridDim = dim3(128); cfg.blockDim = dim3(320); cfg.dynamicSmemBytes = K3_SMEM;
  cudaLaunchKernelEx(&cfg, out_kernel, toa, tob, (__nv_bfloat16*)d_out);
}
```

```cpp
#include <cuda_runtime.h>
#include <cuda_bf16.h>
#include <cuda.h>
#include <stdint.h>

namespace {
constexpr int S_ = 2048, D_ = 512, H_ = 32;
constexpr float QSCALE = 0.25f * 1.4426950408889634f;

__device__ __align__(128) uint4 g_qkv[2][3][H_][2][S_];
__device__ __align__(128) float g_nrm[2][3][H_][128];
__device__ __align__(128) float g_gate[S_];
__device__ __align__(128) uint4 g_o[S_ / 64][64][8][2][8];
constexpr int C_QKV = 0;
constexpr int C_GATE = 16;
constexpr int C_OUT = 32;
constexpr int C_DONE = 64;
constexpr int CS = 64;
__device__ __align__(128) int g_cnt[(C_DONE + 1) * CS];

__device__ __forceinline__ uint32_t smem_u32(const void* p) { return (uint32_t)__cvta_generic_to_shared(p); }
__device__ __forceinline__ void mbar_init(uint32_t bar, int cnt) { asm volatile("mbarrier.init.shared::cta.b64 [%0], %1;" ::"r"(bar), "r"(cnt)); }
__device__ __forceinline__ void mbar_expect(uint32_t bar, uint32_t bytes) { asm volatile("mbarrier.arrive.expect_tx.shared::cta.b64 _, [%0], %1;" ::"r"(bar), "r"(bytes) : "memory"); }
__device__ __forceinline__ void mbar_arrive(uint32_t bar) { asm volatile("mbarrier.arrive.shared::cta.b64 _, [%0];" ::"r"(bar) : "memory"); }
__device__ __forceinline__ void mbar_arrive_cluster(uint32_t bar, uint32_t cta) {
  asm volatile("{\n.reg .b32 ra;\nmapa.shared::cluster.u32 ra, %0, %1;\nmbarrier.arrive.shared::cluster.b64 _, [ra];\n}" ::"r"(bar), "r"(cta) : "memory");
}
constexpr uint32_t WAIT_LIMIT = 40000000;
#define HINT_NS "100000"
#define MBAR_WAIT_ASM(QUAL)                                                                                      \
  asm volatile("{\n.reg .pred p;\n.reg .u32 t0, t;\n"                                                             \
               "mbarrier.try_wait.parity" QUAL ".shared::cta.b64 p, [%0], %1;\n@p bra.uni DONE;\n"                \
               "mov.u32 t0, %%clock;\n"                                                                           \
               "LOOP:\n"                                                                                          \
               "mbarrier.try_wait.parity" QUAL ".shared::cta.b64 p, [%0], %1, " HINT_NS ";\n@p bra.uni DONE;\n"   \
               "mov.u32 t, %%clock;\nsub.u32 t, t, t0;\nsetp.lt.u32 p, t, %2;\n@p bra.uni LOOP;\n"                \
               "DONE:\n}" ::"r"(bar), "r"(parity), "n"(WAIT_LIMIT) : "memory")
__device__ __forceinline__ void mbar_wait(uint32_t bar, uint32_t parity) { MBAR_WAIT_ASM(""); }
__device__ __forceinline__ void mbar_wait_cluster(uint32_t bar, uint32_t parity) { MBAR_WAIT_ASM(".acquire.cluster"); }
__device__ __forceinline__ void bulk_load(uint32_t dst, const void* src, uint32_t bytes, uint32_t bar) {
  asm volatile("cp.async.bulk.shared::cluster.global.mbarrier::complete_tx::bytes [%0], [%1], %2, [%3];" ::"r"(dst), "l"(src), "r"(bytes), "r"(bar) : "memory");
}
__device__ __forceinline__ void tma_2d(uint32_t dst, const CUtensorMap* tm, int c0, int c1, uint32_t bar) {
  asm volatile("cp.async.bulk.tensor.2d.shared::cluster.global.mbarrier::complete_tx::bytes [%0], [%1, {%3, %4}], [%2];" ::"r"(dst), "l"(tm), "r"(bar), "r"(c0), "r"(c1) : "memory");
}
__device__ __forceinline__ void tma_2d_mc(uint32_t dst, const CUtensorMap* tm, int c0, int c1, uint32_t bar, uint16_t mask) {
  asm volatile("cp.async.bulk.tensor.2d.shared::cluster.global.mbarrier::complete_tx::bytes.multicast::cluster [%0], [%1, {%3, %4}], [%2], %5;" ::"r"(dst), "l"(tm), "r"(bar), "r"(c0), "r"(c1), "h"(mask) : "memory");
}
__device__ __forceinline__ void cluster_sync_relaxed() { asm volatile("barrier.cluster.arrive.relaxed.aligned;\nbarrier.cluster.wait.aligned;" ::: "memory"); }
#define WG_FENCE() asm volatile("wgmma.fence.sync.aligned;" ::: "memory")
#define WG_COMMIT() asm volatile("wgmma.commit_group.sync.aligned;" ::: "memory")
#define WG_WAIT(n) asm volatile("wgmma.wait_group.sync.aligned " #n ";" ::: "memory")

template <int N> __device__ __forceinline__ void fence_regs(float (&r)[N]) {
#pragma unroll
  for (int i = 0; i < N; i++) asm volatile("" : "+f"(r[i])::"memory");
}
template <int N> __device__ __forceinline__ void fence_regs(uint32_t (&r)[N]) {
#pragma unroll
  for (int i = 0; i < N; i++) asm volatile("" : "+r"(r[i])::"memory");
}
__device__ __forceinline__ uint32_t pack_bf16(float lo, float hi) {
  uint32_t r; asm("cvt.rn.bf16x2.f32 %0, %1, %2;" : "=r"(r) : "f"(hi), "f"(lo)); return r;
}
__device__ __forceinline__ float ex2(float x) { float r; asm("ex2.approx.ftz.f32 %0, %1;" : "=f"(r) : "f"(x)); return r; }
__device__ __forceinline__ uint64_t make_desc(uint32_t addr, uint32_t lbo, uint32_t sbo, uint32_t swz) {
  return (uint64_t)((addr & 0x3FFFF) >> 4) | ((uint64_t)(lbo >> 4) << 16) | ((uint64_t)(sbo >> 4) << 32) | ((uint64_t)swz << 62);
}

__device__ __forceinline__ void wgmma_n128(float (&d)[64], uint64_t da, uint64_t db, int acc) {
  asm volatile(
      "{\n.reg .pred p;\nsetp.ne.b32 p, %66, 0;\n"
      "wgmma.mma_async.sync.aligned.m64n128k16.f32.bf16.bf16 "
      "{%0,%1,%2,%3,%4,%5,%6,%7,%8,%9,%10,%11,%12,%13,%14,%15,%16,%17,%18,%19,%20,%21,%22,%23,%24,%25,%26,%27,%28,%29,%30,%31,%32,%33,%34,%35,%36,%37,%38,%39,%40,%41,%42,%43,%44,%45,%46,%47,%48,%49,%50,%51,%52,%53,%54,%55,%56,%57,%58,%59,%60,%61,%62,%63}, "
      "%64, %65, p, 1, 1, 0, 1;\n}\n"
      : "+f"(d[0]), "+f"(d[1]), "+f"(d[2]), "+f"(d[3]), "+f"(d[4]), "+f"(d[5]), "+f"(d[6]), "+f"(d[7]),
        "+f"(d[8]), "+f"(d[9]), "+f"(d[10]), "+f"(d[11]), "+f"(d[12]), "+f"(d[13]), "+f"(d[14]), "+f"(d[15]),
        "+f"(d[16]), "+f"(d[17]), "+f"(d[18]), "+f"(d[19]), "+f"(d[20]), "+f"(d[21]), "+f"(d[22]), "+f"(d[23]),
        "+f"(d[24]), "+f"(d[25]), "+f"(d[26]), "+f"(d[27]), "+f"(d[28]), "+f"(d[29]), "+f"(d[30]), "+f"(d[31]),
        "+f"(d[32]), "+f"(d[33]), "+f"(d[34]), "+f"(d[35]), "+f"(d[36]), "+f"(d[37]), "+f"(d[38]), "+f"(d[39]),
        "+f"(d[40]), "+f"(d[41]), "+f"(d[42]), "+f"(d[43]), "+f"(d[44]), "+f"(d[45]), "+f"(d[46]), "+f"(d[47]),
        "+f"(d[48]), "+f"(d[49]), "+f"(d[50]), "+f"(d[51]), "+f"(d[52]), "+f"(d[53]), "+f"(d[54]), "+f"(d[55]),
        "+f"(d[56]), "+f"(d[57]), "+f"(d[58]), "+f"(d[59]), "+f"(d[60]), "+f"(d[61]), "+f"(d[62]), "+f"(d[63])
      : "l"(da), "l"(db), "r"(acc));
}

__device__ __forceinline__ void k1_store_group(const float (&acc)[64], int j, float sc, uint32_t* dst) {
  float v[8];
#pragma unroll
  for (int e = 0; e < 8; e++) v[e] = acc[8 * j + e] * sc;
  uint32_t* p = dst + ((j & 3) + (j >> 2) * 32) * (8 * S_);
  p[0] = pack_bf16(v[0], v[1]); p[32] = pack_bf16(v[2], v[3]); p[4 * S_] = pack_bf16(v[4], v[5]); p[4 * S_ + 32] = pack_bf16(v[6], v[7]);
}
__device__ __forceinline__ void k1_park_group(const float (&acc)[64], int j, float sc, uint32_t addr) {
  float v[8];
#pragma unroll
  for (int e = 0; e < 8; e++) v[e] = acc[8 * j + e] * sc;
  asm volatile("stmatrix.sync.aligned.m8n8.x4.shared.b16 [%0], {%1,%2,%3,%4};" ::"r"(addr + (j & 3) * 2048), "r"(pack_bf16(v[0], v[1])),
               "r"(pack_bf16(v[2], v[3])), "r"(pack_bf16(v[4], v[5])), "r"(pack_bf16(v[6], v[7])) : "memory");
}
template <int J0, int J1>
__device__ __forceinline__ float k1_norms(const float (&acc)[64], int lane) {
  float t[8];
#pragma unroll
  for (int j = J0; j < J1; j++) {
    const float* v = acc + 8 * j;
    const float s0 = fmaf(v[0], v[0], fmaf(v[1], v[1], fmaf(v[4], v[4], v[5] * v[5])));
    const float s1 = fmaf(v[2], v[2], fmaf(v[3], v[3], fmaf(v[6], v[6], v[7] * v[7])));
    t[j] = ((lane & 1) ? s1 : s0) + __shfl_xor_sync(0xffffffff, (lane & 1) ? s0 : s1, 1);
  }
  int nm = 0;
#pragma unroll
  for (int j = J0; j < J1; j++) {
    t[j] += __shfl_xor_sync(0xffffffff, t[j], 2);
    const int m = __reduce_max_sync(0xffffffff, __float_as_int(t[j]));
    nm = lane == j ? m : nm;
  }
  return __int_as_float(nm);
}

__device__ __forceinline__ void wgmma_s64(float (&d)[32], const uint32_t (&a)[4], uint64_t desc) {
  asm volatile(
      "wgmma.mma_async.sync.aligned.m64n64k16.f32.bf16.bf16 "
      "{%0,%1,%2,%3,%4,%5,%6,%7,%8,%9,%10,%11,%12,%13,%14,%15,%16,%17,%18,%19,%20,%21,%22,%23,%24,%25,%26,%27,%28,%29,%30,%31}, "
      "{%32,%33,%34,%35}, %36, 0, 1, 1, 0;\n"
      : "+f"(d[0]), "+f"(d[1]), "+f"(d[2]), "+f"(d[3]), "+f"(d[4]), "+f"(d[5]), "+f"(d[6]), "+f"(d[7]),
        "+f"(d[8]), "+f"(d[9]), "+f"(d[10]), "+f"(d[11]), "+f"(d[12]), "+f"(d[13]), "+f"(d[14]), "+f"(d[15]),
        "+f"(d[16]), "+f"(d[17]), "+f"(d[18]), "+f"(d[19]), "+f"(d[20]), "+f"(d[21]), "+f"(d[22]), "+f"(d[23]),
        "+f"(d[24]), "+f"(d[25]), "+f"(d[26]), "+f"(d[27]), "+f"(d[28]), "+f"(d[29]), "+f"(d[30]), "+f"(d[31])
      : "r"(a[0]), "r"(a[1]), "r"(a[2]), "r"(a[3]), "l"(desc));
}
__device__ __forceinline__ void wgmma_pv(float (&o)[12], uint32_t a0, uint32_t a1, uint32_t a2, uint32_t a3, uint64_t desc) {
  asm volatile(
      "wgmma.mma_async.sync.aligned.m64n24k16.f32.bf16.bf16 "
      "{%0,%1,%2,%3,%4,%5,%6,%7,%8,%9,%10,%11}, {%12,%13,%14,%15}, %16, 1, 1, 1, 1;\n"
      : "+f"(o[0]), "+f"(o[1]), "+f"(o[2]), "+f"(o[3]), "+f"(o[4]), "+f"(o[5]), "+f"(o[6]), "+f"(o[7]), "+f"(o[8]), "+f"(o[9]), "+f"(o[10]), "+f"(o[11])
      : "r"(a0), "r"(a1), "r"(a2), "r"(a3), "l"(desc));
}
__device__ __forceinline__ void issue_pv(float (&o)[12], const uint32_t (&p)[16], uint64_t dv) {
#pragma unroll
  for (int i = 0; i < 4; i++) wgmma_pv(o, p[4 * i], p[4 * i + 1], p[4 * i + 2], p[4 * i + 3], dv + i * 16);
}

constexpr int MUFU_MASK = 0xFC00;
__device__ __forceinline__ uint32_t exp_fma_pair(float x0, float x1, uint32_t one2  ) {
  const float M0 = 65536.0f + 127.0f - 1.6015625f, M1 = 66032.0f - 1.6015625f;
  const uint32_t t0 = __float_as_uint(x0 + M0), t1 = __float_as_uint(x1 + M1);
  const uint32_t w = t1 * 65536u + t0;
  uint32_t u, d;
  asm("lop3.b32 %0, %1, 0x007F007F, %2, 0xEA;" : "=r"(u) : "r"(w), "r"(one2));
  asm("fma.rn.bf16x2 %0, %1, %1, %2;" : "=r"(d) : "r"(u), "r"(0x40034003u));
  return d + w - u;
}
__device__ __forceinline__ void exp_tile(const float (&s)[32], uint32_t (&p)[16], uint32_t cu) {
  float e[32];
#pragma unroll
  for (int m = 0; m < 16; m++) if ((MUFU_MASK >> m) & 1) { e[2 * m] = ex2(s[2 * m]); e[2 * m + 1] = ex2(s[2 * m + 1]); }
#pragma unroll
  for (int m = 0; m < 16; m++) if (!((MUFU_MASK >> m) & 1)) p[m] = exp_fma_pair(s[2 * m], s[2 * m + 1], cu);
#pragma unroll
  for (int m = 0; m < 16; m++) if ((MUFU_MASK >> m) & 1) p[m] = pack_bf16(e[2 * m], e[2 * m + 1]);
}
constexpr int EDGE_MASK = 0x9249;
template <bool FAR>
__device__ __forceinline__ void exp_edge(const float (&s)[32], uint32_t (&p)[16], uint32_t cu, int warp, int lane) {
  const int d = (lane >> 2) - 2 * (lane & 3);
  uint32_t tri = d >= 1 ? 0xFFFFFFFFu : (d == 0 ? 0x0000FFFFu : 0u);
  if (FAR) tri = ~tri;
#pragma unroll
  for (int b = 0; b < 4; b++) {
    if (FAR ? b >= warp : b <= warp) {
#pragma unroll
      for (int m = 4 * b; m < 4 * b + 4; m++) {
        if ((EDGE_MASK >> m) & 1) p[m] = pack_bf16(ex2(s[2 * m]), ex2(s[2 * m + 1]));
        else p[m] = exp_fma_pair(s[2 * m], s[2 * m + 1], cu);
      }
      if (b == warp) {
        p[4 * b] &= tri; p[4 * b + 3] &= tri;
        if (FAR) p[4 * b + 1] = 0; else p[4 * b + 2] = 0;
      }
    } else {
      p[4 * b] = p[4 * b + 1] = p[4 * b + 2] = p[4 * b + 3] = 0;
    }
  }
}

__device__ __forceinline__ void hmma(float* d, const uint32_t* a, uint32_t b0, uint32_t b1) {
  asm("mma.sync.aligned.m16n8k16.row.col.f32.bf16.bf16.f32 {%0,%1,%2,%3}, {%4,%5,%6,%7}, {%8,%9}, {%0,%1,%2,%3};"
      : "+f"(d[0]), "+f"(d[1]), "+f"(d[2]), "+f"(d[3]) : "r"(a[0]), "r"(a[1]), "r"(a[2]), "r"(a[3]), "r"(b0), "r"(b1));
}
__device__ __forceinline__ void safe_chunk(float (&o)[12], float& m0, float& m1, const uint32_t (&q)[4], uint32_t klo, uint32_t khi, uint32_t vlo,
                                           uint32_t vhi, int lane, int dbase, int mode) {
  const float ninf = __int_as_float(0xFF800000);
  float t[16];
  uint32_t p[8];
#pragma unroll
  for (int j = 0; j < 4; j++) {
    uint32_t b0, b1;
    asm volatile("ld.shared.u32 %0, [%1];" : "=r"(b0) : "r"(klo + j * 128 + lane * 4));
    asm volatile("ld.shared.u32 %0, [%1];" : "=r"(b1) : "r"(khi + j * 128 + lane * 4));
    t[4 * j] = t[4 * j + 1] = t[4 * j + 2] = t[4 * j + 3] = 0.f;
    hmma(t + 4 * j, q, b0, b1);
  }
  float x0 = m0, x1 = m1;
#pragma unroll
  for (int i = 0; i < 16; i++) {
    const int d = dbase + 8 * ((i >> 1) & 1) - 8 * (i >> 2) - (i & 1);
    const bool keep = mode == 0 || (mode == 1 ? d < 0 : d >= 0);
    t[i] = keep ? t[i] : ninf;
    if ((i >> 1) & 1) x1 = fmaxf(x1, t[i]); else x0 = fmaxf(x0, t[i]);
  }
  x0 = fmaxf(x0, __shfl_xor_sync(0xffffffff, x0, 1)); x0 = fmaxf(x0, __shfl_xor_sync(0xffffffff, x0, 2));
  x1 = fmaxf(x1, __shfl_xor_sync(0xffffffff, x1, 1)); x1 = fmaxf(x1, __shfl_xor_sync(0xffffffff, x1, 2));
  const float y0 = x0 == ninf ? 0.f : x0, y1 = x1 == ninf ? 0.f : x1;
  const float r0 = ex2(m0 - y0), r1 = ex2(m1 - y1);
  m0 = x0; m1 = x1;
#pragma unroll
  for (int i = 0; i < 12; i++) o[i] *= ((i >> 1) & 1) ? r1 : r0;
#pragma unroll
  for (int m = 0; m < 8; m++) { const float y = (m & 1) ? y1 : y0; p[m] = pack_bf16(ex2(t[2 * m] - y), ex2(t[2 * m + 1] - y)); }
#pragma unroll
  for (int i = 0; i < 2; i++) {
    uint32_t v0, v1, v2, v3;
    const uint32_t addr = ((lane & 16) ? vhi : vlo) + i * 256 + (lane & 15) * 16;
    asm volatile("ldmatrix.sync.aligned.m8n8.x4.trans.shared.b16 {%0,%1,%2,%3}, [%4];" : "=r"(v0), "=r"(v1), "=r"(v2), "=r"(v3) : "r"(addr));
    hmma(o, p + 4 * i, v0, v1);
    hmma(o + 4, p + 4 * i, 0x3F803F80u, 0x3F803F80u);
    hmma(o + 8, p + 4 * i, v2, v3);
  }
}

constexpr int G = 8192;
constexpr int K1_NST = 6, SM_W = 16 * G;
__host__ __device__ constexpr int sm_klo(int q) { return (3 + 2 * q) * G; }
__host__ __device__ constexpr int sm_vlo(int q) { return q ? (19 - q) * G : 0; }
__host__ __device__ constexpr int sm_vhi(int q) { return q ? (20 + q) * G : 2 * G; }
constexpr int SM_ONE0 = G, SM_ONE1 = 19 * G, SM_KB = 11 * G, SM_VBLO = 14 * G, SM_VBHI = 24 * G, SM_QB = 26 * G, SM_GATE = SM_ONE1 + 12288;
constexpr int SM_QA1 = SM_VBLO + 12288, QA1_HI = SM_VBHI - SM_VBLO;
__host__ __device__ constexpr int wo_slot(int i) { constexpr int t[16] = {11, 12, 13, 14, 15, 24, 25, 26, 0, 27, 1, 2, 3, 4, 5, 6}; return t[i] * G; }
__host__ __device__ constexpr int a_slot(int i) { constexpr int t[8] = {18, 21, 7, 8, 17, 22, 9, 10}; return t[i] * G; }
__host__ __device__ constexpr int x_slot(int i) { constexpr int t[4] = {16, 19, 20, 23}; return t[i] * G; }
constexpr int SM_BAR = 28 * G;
enum { B_FULL = 0, B_EMPTY = 24, B_X = 30, B_XDEAD = 38, B_GDONE, B_SEENA, B_STA, B_STB, B_OKA, B_OKB, B_RND, B_RND1, B_PARK, B_EARLY, B_FREE, B_LATE, B_LATE3 = B_LATE + 3, B_PC, B_LAST = B_PC + 5, B_Q0D, B_Q1D, B_Q2D, B_DONE, B_PEER, B_WO,
       B_AF, B_XCH = B_AF + 8, B_COUNT = B_XCH + 8 };
constexpr int SM_EVT = SM_BAR + 768;
constexpr int SM_TOTAL = SM_BAR + 896;
static_assert(B_COUNT <= 96, "");

__device__ __forceinline__ void wg_sync(int wg) { asm volatile("bar.sync %0, 128;" ::"r"(wg + 1) : "memory"); }
__device__ __forceinline__ void count(int c) { asm volatile("red.relaxed.gpu.global.add.s32 [%0], 1;" ::"l"(&g_cnt[c * CS]) : "memory"); }
__device__ __forceinline__ void await(int c, int n) {
  int v;
  const uint32_t t0 = clock();
  do {
    asm volatile("ld.acquire.gpu.global.s32 %0, [%1];" : "=r"(v) : "l"(&g_cnt[c * CS]) : "memory");
  } while (v < n && (uint32_t)clock() - t0 < (uint32_t)WAIT_LIMIT);
  asm volatile("fence.proxy.async.global;" ::: "memory");
}
__device__ __forceinline__ int read_flag(uint32_t addr) {
  int v;
  asm volatile("ld.shared.u32 %0, [%1];" : "=r"(v) : "r"(addr) : "memory");
  return __shfl_sync(0xffffffff, v, 0);
}

__device__ __forceinline__ void st_relaxed(uint32_t* p, uint32_t v) { asm volatile("st.relaxed.gpu.global.u32 [%0], %1;" ::"l"(p), "r"(v) : "memory"); }
constexpr uint32_t EMPTY = 0xFFFFFFFFu;
__device__ __forceinline__ void load_q(uint32_t (&q)[4], int br, int h, int row0, int warp, int lane) {
  const uint32_t* p = reinterpret_cast<const uint32_t*>(&g_qkv[br][0][h][0][row0 + warp * 16]) + lane;
  q[0] = __ldcg(p); q[1] = __ldcg(p + 32); q[2] = __ldcg(p + 4 * S_); q[3] = __ldcg(p + 4 * S_ + 32);
}
__device__ __forceinline__ void lds_q(uint32_t (&q)[4], uint32_t addr, int hi) {
  asm volatile("ld.shared.u32 %0, [%1];" : "=r"(q[0]) : "r"(addr));
  asm volatile("ld.shared.u32 %0, [%1];" : "=r"(q[1]) : "r"(addr + 128));
  asm volatile("ld.shared.u32 %0, [%1];" : "=r"(q[2]) : "r"(addr + hi));
  asm volatile("ld.shared.u32 %0, [%1];" : "=r"(q[3]) : "r"(addr + hi + 128));
}
__device__ __forceinline__ float2 load_gate(uint32_t sb, int br, int row0, int warp, int lane) {
  float2 g;
  const uint32_t ga = sb + SM_GATE + ((row0 & 511) + warp * 16 + (lane >> 2)) * 4;
  asm volatile("ld.shared.f32 %0, [%1];" : "=f"(g.x) : "r"(ga));
  asm volatile("ld.shared.f32 %0, [%1];" : "=f"(g.y) : "r"(ga + 32));
  if (br) { g.x = 1.0f - g.x; g.y = 1.0f - g.y; }
  return g;
}
__device__ __forceinline__ float rcp(float x) { float r; asm("rcp.approx.ftz.f32 %0, %1;" : "=f"(r) : "f"(x)); return r; }
__device__ __forceinline__ void store_o(const float (&o)[12], float2 g, int br, int h, int row0, int warp, int lane) {
  const float s0 = g.x * rcp(o[4]), s1 = g.y * rcp(o[6]);
  uint32_t* dst = reinterpret_cast<uint32_t*>(&g_o[row0 >> 6][br * 32 + h][warp * 2][0][0]) + lane;
  st_relaxed(dst, pack_bf16(o[0] * s0, o[1] * s0));
  st_relaxed(dst + 64, pack_bf16(o[2] * s1, o[3] * s1));
  st_relaxed(dst + 32, pack_bf16(o[8] * s0, o[9] * s0));
  st_relaxed(dst + 96, pack_bf16(o[10] * s1, o[11] * s1));
}
__device__ __forceinline__ bool range_ok(int br, int h, int qb, int lane) {
  const int qn = __float_as_int(__ldcg(&g_nrm[br][0][h][qb * 32 + lane]));
  const int4 k4 = __ldcg(reinterpret_cast<const int4*>(g_nrm[br][1][h]) + lane), v4 = __ldcg(reinterpret_cast<const int4*>(g_nrm[br][2][h]) + lane);
  const int kn = max(max(k4.x, k4.y), max(k4.z, k4.w)), vn = max(max(v4.x, v4.y), max(v4.z, v4.w));
  const float q2 = __int_as_float(__reduce_max_sync(0xffffffff, qn));
  const float k2 = __int_as_float(__reduce_max_sync(0xffffffff, kn));
  const float v2 = __int_as_float(__reduce_max_sync(0xffffffff, vn));
  return (q2 * k2 <= 8100.0f) & (v2 <= 1.0e12f) & (v2 >= 6.0e-8f);
}

__device__ __noinline__ void safe_tile(uint32_t sb, int br, int h, int row0) {
  const int lane = threadIdx.x & 31, warp = (threadIdx.x >> 5) & 3;
  const int dbase = warp * 16 + (lane >> 2) - 2 * (lane & 3), t = (row0 >> 6) & 7;
  uint32_t q[4];
  load_q(q, br, h, row0, warp, lane);
  float m0 = __int_as_float(0xFF800000), m1 = m0, o[12];
#pragma unroll
  for (int i = 0; i < 12; i++) o[i] = 0.f;
#pragma unroll 1
  for (int c2 = br ? 2 * max(t, row0 < 512 ? 4 : 0) : 0; c2 < (br ? 2 * t + 10 : 64); c2++) {
    const int c = c2 >> 1, qt = c2 >> 4, off = br ? c2 * 512 : (c2 & 15) * 512;
    if (!br) mbar_wait(sb + SM_BAR + 8 * (B_PC + qt), 0);
    const uint32_t klo = sb + off + (br ? SM_KB : (3 + 2 * qt) * G);
    safe_chunk(o, m0, m1, q, klo, klo + (br ? 12288 : G), sb + off + (br ? SM_VBLO : (qt ? 19 - qt : 0) * G),
               sb + off + (br ? SM_VBHI : (qt ? 20 + qt : 2) * G), lane, dbase - 32 * (c2 & 1), br ? (c == t ? 1 : (c == t + 4 ? 2 : 0)) : 0);
  }
  store_o(o, load_gate(sb, br, row0, warp, lane), br, h, row0, warp, lane);
}

__global__ void __cluster_dims__(2, 1, 1) __launch_bounds__(640, 1)
fused_kernel(const __grid_constant__ CUtensorMap tm_x, const __grid_constant__ CUtensorMap tm_wa, const __grid_constant__ CUtensorMap tm_wb,
             const __grid_constant__ CUtensorMap tm_oa, const __grid_constant__ CUtensorMap tm_ob,
             const __grid_constant__ CUtensorMap tm_st, const __nv_bfloat16* __restrict__ gw,
             __nv_bfloat16* __restrict__ out, int opq) {
  extern __shared__ __align__(1024) uint8_t smem[];
  const uint32_t sb = smem_u32(smem);
  const uint32_t bar = sb + SM_BAR;
#define BAR(i) (bar + 8 * (i))
  const int tid = threadIdx.x, lane = tid & 31;
  const int wid = __shfl_sync(0xffffffff, tid >> 5, 0), wg = wid >> 2, warp = __shfl_sync(0xffffffff, (tid >> 5) & 3, 0);
  const int bid = blockIdx.x, rank = bid & 1;
  const int mblk1 = bid & 15, nt = bid >> 4;
  const int h = bid >> 2, qb = bid & 3;
  const int nblk = (bid >> 1) & 3, mblk3 = bid >> 3;
  if (tid == 512) {
    for (int i = 0; i < 2; i++) { mbar_init(BAR(B_X + i), 1); mbar_init(BAR(B_FULL + i), 1); }
    asm volatile("fence.mbarrier_init.release.cluster;" ::: "memory");
    for (int i = 0; i < 2; i++) {
      mbar_expect(BAR(B_X + i), 16384);
      tma_2d(sb + i * 16384, &tm_x, i * 64, mblk1 * 128, BAR(B_X + i));
      mbar_expect(BAR(B_FULL + i), 16384);
      for (int m = 0; m < 2; m++) tma_2d(sb + SM_W + i * 16384 + m * 8192, &tm_wa, m * 512 + nt * 64, i * 64, BAR(B_FULL + i));
    }
  } else if (wid < 16 && lane == 0) {
#pragma unroll
    for (int j = 0; j < 6; j++) {
      const int i = wid + 16 * j;
      if (i >= B_COUNT || i == B_X || i == B_X + 1 || i < B_FULL + 2) continue;
      int c = 1;
      if (i >= B_EMPTY && i < B_X) c = 4;
      if (i == B_GDONE || i == B_RND || i == B_RND + 1 || i == B_PC || i == B_PC + 1 || i == B_PC + 4) c = 2;
      if (i == B_XDEAD) c = 4;
      if (i >= B_LAST && i <= B_DONE) c = 16;
      if (i == B_PEER || i == B_FREE || (i >= B_LATE && i <= B_LATE3)) c = 4;
      if (i == B_STA) c = 18;
      if (i == B_STB) c = 16;
      if (i == B_WO) c = 3;
      mbar_init(BAR(i), c);
      if (i >= B_XCH) mbar_expect(BAR(i), 4096);
    }
    asm volatile("fence.mbarrier_init.release.cluster;" ::: "memory");
  }
  __syncthreads();
  cluster_sync_relaxed();

  if (wg == 4) {
    asm volatile("setmaxnreg.dec.sync.aligned.u32 32;");
    if (tid == 512) {
#pragma unroll 1
      for (int it = 2; it < 24; it++) {
        const int s = it % K1_NST, m = (it >> 3) * 2 + rank, kb = it & 7;
        if (it < 8) { mbar_expect(BAR(B_X + it), 16384); tma_2d(sb + it * 16384, &tm_x, it * 64, mblk1 * 128, BAR(B_X + it)); }
        if (it >= K1_NST) mbar_wait(BAR(B_EMPTY + s), (it / K1_NST - 1) & 1);
        mbar_expect(BAR(B_FULL + it), 16384);
        tma_2d_mc(sb + SM_W + s * 16384 + rank * 8192, m >= 3 ? &tm_wb : &tm_wa, (m >= 3 ? m - 3 : m) * 512 + nt * 64, kb * 64,
                  BAR(B_FULL + it), 3);
      }
      await(C_QKV + (h >> 2), 16);
      mbar_arrive(BAR(B_SEENA));
      mbar_wait(BAR(B_XDEAD), 0);
#pragma unroll
      for (int q = 0; q < 4; q++) {
        if (q == 1) { mbar_wait(BAR(B_GDONE), 0); await(C_GATE, 128); }
        if (q == 2) mbar_wait(BAR(B_PARK), 0);
        mbar_expect(BAR(B_PC + q), 4 * G + (q == 1 ? 2048 : 0));
        bulk_load(sb + sm_klo(q), &g_qkv[0][1][h][0][q * 512], G, BAR(B_PC + q));
        bulk_load(sb + sm_klo(q) + G, &g_qkv[0][1][h][1][q * 512], G, BAR(B_PC + q));
        bulk_load(sb + sm_vlo(q), &g_qkv[0][2][h][0][q * 512], G, BAR(B_PC + q));
        bulk_load(sb + sm_vhi(q), &g_qkv[0][2][h][1][q * 512], G, BAR(B_PC + q));
        if (q == 1) bulk_load(sb + SM_GATE, &g_gate[qb * 512], 2048, BAR(B_PC + q));
      }
      await(C_QKV + 8 + (h >> 2), 16);
      {
        const int c0 = qb == 0 ? 4 : 0, k0 = 512 * qb - 256 + 64 * c0, n = (768 - 64 * c0) * 16;
        const uint32_t b = BAR(B_PC + 4);
        mbar_expect(b, 4 * n + 3 * G);
#pragma unroll 1
        for (int i = 0; i < 8; i++) bulk_load(sb + SM_QA1 + (i >> 2) * QA1_HI + (i & 3) * 1024, &g_qkv[0][0][h][i >> 2][qb * 512 + (i & 3) * 128 + 64], 1024, b);
        bulk_load(sb + SM_QB, &g_qkv[1][0][h][0][qb * 512], G, b);
        bulk_load(sb + SM_QB + G, &g_qkv[1][0][h][1][qb * 512], G, b);
        bulk_load(sb + SM_KB + c0 * 1024, &g_qkv[1][1][h][0][k0], n, b);
        bulk_load(sb + SM_KB + 12288 + c0 * 1024, &g_qkv[1][1][h][1][k0], n, b);
        bulk_load(sb + SM_VBLO + c0 * 1024, &g_qkv[1][2][h][0][k0], n, b);
        bulk_load(sb + SM_VBHI + c0 * 1024, &g_qkv[1][2][h][1][k0], n, b);
      }
#define WO_BOX(i) tma_2d(sb + wo_slot(i), (i) < 8 ? &tm_ob : &tm_oa, nblk * 128 + ((((i) & 1) ^ rank) << 6), rank * 256 + (((i) >> 1) & 3) * 64, BAR(B_WO))
#define A_LOAD(i) { mbar_expect(BAR(B_AF + (i)), G); bulk_load(sb + a_slot(i), &g_o[mblk3 * 2 + ((i) & 1)][32 + rank * 16 + ((i) >> 1) * 4][0][0][0], G, BAR(B_AF + (i))); }
      mbar_wait(BAR(B_LAST), 0);
      asm volatile("fence.acq_rel.gpu;" ::: "memory");
      for (int w = 0; w < 4; w++) count(C_OUT + (qb * 4 + w) * 2 + (h >> 4));
      mbar_expect(BAR(B_WO), 9 * G);
      WO_BOX(0); WO_BOX(1); WO_BOX(2); WO_BOX(3); WO_BOX(4); WO_BOX(5); WO_BOX(6); WO_BOX(7); WO_BOX(9);
      mbar_wait(BAR(B_Q0D), 0);
      mbar_expect(BAR(B_WO), 5 * G);
      WO_BOX(8); WO_BOX(10); WO_BOX(11); WO_BOX(12); WO_BOX(13);
      mbar_wait(BAR(B_Q1D), 0);
      mbar_expect(BAR(B_WO), 2 * G);
      WO_BOX(14); WO_BOX(15);
      await(C_OUT + mblk3 * 2 + rank, 16);
      mbar_arrive(BAR(B_EARLY));
      if (atomicAdd(&g_cnt[C_DONE * CS], 1) == 127) {
        for (int j = 0; j <= C_DONE; j++) g_cnt[j * CS] = 0;
      }
      A_LOAD(0); A_LOAD(1);
      mbar_wait(BAR(B_Q2D), 0);
      A_LOAD(2); A_LOAD(3); A_LOAD(4); A_LOAD(5);
      mbar_wait(BAR(B_DONE), 0);
      A_LOAD(6); A_LOAD(7);
#undef WO_BOX
#undef A_LOAD
    } else if (warp) {
      if (warp == 1 && lane == 0) asm volatile("prefetch.tensormap [%0];" ::"l"(&tm_wb) : "memory");
      if (warp >= 2) {
        const int r = nt * 16 + (warp - 2) * 8 + (lane >> 2);
        float s0 = 0.f, s1 = 0.f;
#pragma unroll 1
        for (int kb = 0; kb < 8; kb++) {
          mbar_wait(BAR(B_X + kb), 0);
#pragma unroll
          for (int u = 0; u < 2; u++) {
            const int ch = (lane & 3) * 2 + u;
            const uint4 w = __ldg(reinterpret_cast<const uint4*>(gw) + kb * 8 + ch);
            uint4 a;
            asm volatile("ld.shared.v4.u32 {%0,%1,%2,%3}, [%4];" : "=r"(a.x), "=r"(a.y), "=r"(a.z), "=r"(a.w) : "r"(sb + kb * 16384 + r * 128 + (((ch ^ r) & 7) << 4)));
            const uint32_t av[4] = {a.x, a.y, a.z, a.w}, wv[4] = {w.x, w.y, w.z, w.w};
#pragma unroll
            for (int j = 0; j < 4; j++) {
              s0 = fmaf(__uint_as_float(av[j] << 16), __uint_as_float(wv[j] << 16), s0);
              s1 = fmaf(__uint_as_float(av[j] & 0xFFFF0000u), __uint_as_float(wv[j] & 0xFFFF0000u), s1);
            }
          }
        }
        s0 += s1;
        s0 += __shfl_xor_sync(0xffffffff, s0, 1);
        s0 += __shfl_xor_sync(0xffffffff, s0, 2);
        if ((lane & 3) == 0) g_gate[mblk1 * 128 + r] = 1.0f / (1.0f + __expf(-s0));
        __syncwarp();
        if (lane == 0) { mbar_arrive(BAR(B_XDEAD)); mbar_arrive(BAR(B_STA)); }
      }
      if (lane == 0 && warp < 3) {
        mbar_wait(BAR(B_STA + warp - 1), 0);
        if (warp == 2) {
          mbar_wait(BAR(B_PC), 0);
#pragma unroll
          for (int i = 0; i < 6; i++)
            asm volatile("cp.async.bulk.tensor.2d.global.shared::cta.bulk_group [%0, {%1, %2}], [%3];" ::"l"(&tm_st), "r"((mblk1 * 128 + (i & 1) * 64) * 4),
                         "r"(((3 + (i >> 1)) * 32 + nt * 4) * 2), "r"(sb + (i < 2 ? 16 + i : 10 + i) * G) : "memory");
          asm volatile("cp.async.bulk.commit_group;\ncp.async.bulk.wait_group.read 0;" ::: "memory");
          mbar_arrive(BAR(B_PARK));
          asm volatile("cp.async.bulk.wait_group 0;\nfence.proxy.async.global;" ::: "memory");
        }
        asm volatile("fence.acq_rel.gpu;" ::: "memory");
        count(C_QKV + (warp - 1) * 8 + nt);
        if (warp == 1) count(C_GATE);
      }
      if (warp == 3) {
#pragma unroll 1
        for (int step = 0; step < 3; step++) {
          mbar_wait(BAR(step == 0 ? B_XDEAD : (step == 1 ? B_GDONE : B_PARK)), 0);
          const uint32_t v = step < 2 ? 0x3F803F80u : 0u;
          const int n = step == 0 ? 16 : (step == 1 || qb == 0 ? 24 : 0);
#pragma unroll 1
          for (int i = 0; i < n; i++) {
            const uint32_t base = step == 0 ? SM_ONE0 : (step == 1 ? SM_ONE1 : (i < 8 ? SM_VBLO : (i < 16 ? SM_KB - 4096 : SM_KB + 4096)));
            asm volatile("st.shared.v4.u32 [%0], {%1,%1,%1,%1};" ::"r"(sb + base + i * 512 + lane * 16), "r"(v) : "memory");
          }
          asm volatile("fence.proxy.async.shared::cta;" ::: "memory");
          __syncwarp();
          if (lane == 0) mbar_arrive(BAR(B_PC + step * step));
        }
      }
      if (warp < 3) {
        const int br = warp - 1;
        __syncwarp();
        mbar_wait(BAR(br ? B_PC + 4 : B_SEENA), 0);
        const bool ok = range_ok(br, h, qb, lane);
        if (lane == 0) {
          asm volatile("st.shared.u32 [%0], %1;" ::"r"(sb + SM_EVT + 4 + 4 * br), "r"((uint32_t)ok) : "memory");
          mbar_arrive(BAR(B_OKA + br));
        }
      }
    }
    return;
  }
  asm volatile("setmaxnreg.inc.sync.aligned.u32 112;");

  {
    const int row0 = mblk1 * 128 + (wid & 7) * 16;
    const uint64_t da = make_desc(sb + (wg & 1) * 8192, 16, 1024, 1);
    const uint64_t db = make_desc(sb + SM_W, 8192, 1024, 1);
#pragma unroll 1
    for (int ri = (wg >> 1) ^ 1; ri < 3; ri += 2) {
      const int round = __shfl_sync(0xffffffff, ri, 0);
      float acc[64];
      if (round) { mbar_wait(BAR(B_FULL + round * 8), 0); mbar_wait(BAR(B_RND + round - 1), 0); }
#pragma unroll
      for (int kb = 0; kb < 8; kb++) {
        int st = 2 * round + kb;
        st -= st >= K1_NST ? K1_NST : 0;
        mbar_wait(BAR(B_X + kb), 0);
        mbar_wait(BAR(B_FULL + round * 8 + kb), 0);
        WG_FENCE();
#pragma unroll
        for (int k = 0; k < 4; k++) wgmma_n128(acc, da + kb * 1024 + k * 2, db + st * 1024 + k * 128, (kb | k) != 0);
        WG_COMMIT();
        if (kb == 7 && round < 2 && (tid & 127) == 0) mbar_arrive(BAR(B_RND + round));
        if (kb >= 2) {
          WG_WAIT(2);
          if (round * 8 + kb - 2 < 24 - K1_NST && (tid & 127) < 2) mbar_arrive_cluster(BAR(B_EMPTY + (st >= 2 ? st - 2 : st + 4)), tid & 1);
          if (kb == 3 && round == 2) {
            WG_WAIT(1);
            if ((tid & 127) == 0) mbar_arrive(BAR(B_XDEAD));
          }
        }
      }
      WG_WAIT(0);
      fence_regs(acc);
      if (round < 2) { if ((tid & 127) < 4) mbar_arrive_cluster(BAR(B_EMPTY + 2 * round + ((tid >> 1) & 1)), tid & 1); }
      else if ((tid & 127) == 0) mbar_arrive(BAR(B_GDONE));
      const int g0 = round * 64 + nt * 4;
      uint32_t* dst = reinterpret_cast<uint32_t*>(&g_qkv[0][0][0][0][0] + (size_t)g0 * 2 * S_ + row0) + lane;
      const uint32_t park = sb + (wg & 1) * G + (lane >> 4) * 1024 + warp * 256 + (lane & 15) * 16;
      float* ndst = &g_nrm[0][0][0][0] + (g0 + (lane & 3) + ((lane >> 2) & 1) * 32) * 128 + (row0 >> 4);
      if (round == 0) {
        const uint32_t tp = clock();
#pragma unroll
        for (int j = 0; j < 8; j++) {
          k1_store_group(acc, j, j < 4 ? QSCALE : 1.0f, dst);
          while ((uint32_t)clock() - tp < (j + 1) * 340) __nanosleep(40);
        }
        const float nm = k1_norms<0, 8>(acc, lane);
        if (lane < 8) *ndst = lane < 4 ? nm * (QSCALE * QSCALE) : nm;
        __syncwarp();
        if (lane == 0) mbar_arrive(BAR(B_STA));
      } else if (round == 1) {
#pragma unroll
        for (int j = 0; j < 4; j++) k1_store_group(acc, j, 1.0f, dst);
        const float nv = k1_norms<0, 4>(acc, lane);
        if (lane < 4) *ndst = nv;
        __syncwarp();
        if (lane == 0) mbar_arrive(BAR(B_STA));
        const float nq = k1_norms<4, 8>(acc, lane);
        mbar_wait(BAR(B_XDEAD), 0);
#pragma unroll
        for (int j = 4; j < 8; j++) k1_park_group(acc, j, QSCALE, park + 16 * G);
        asm volatile("fence.proxy.async.shared::cta;" ::: "memory");
        if ((lane >> 2) == 1) *ndst = nq * (QSCALE * QSCALE);
        __syncwarp();
        if (lane == 0) mbar_arrive(BAR(B_STB));
      } else {
        wg_sync(wg);
#pragma unroll
        for (int j = 0; j < 8; j++) k1_park_group(acc, j, 1.0f, park + (12 + 2 * (j >> 2)) * G);
        asm volatile("fence.proxy.async.shared::cta;" ::: "memory");
        const float nm = k1_norms<0, 8>(acc, lane);
        if (lane < 8) *ndst = nm;
        __syncwarp();
        if (lane == 0) mbar_arrive(BAR(B_STB));
      }
    }
  }

  {
    const int rowb = qb * 512 + wg * 128;
    const int cmin = qb == 0 ? 4 : 0;
    uint32_t q[4];
    uint32_t cu;
    asm volatile("mov.b32 %0, %1;" : "=r"(cu) : "r"(opq * 0x3F803F80u));
    mbar_wait(BAR(B_SEENA), 0);
    load_q(q, 0, h, rowb, warp, lane);
    mbar_wait(BAR(B_OKA), 0);
    const bool fast_a = read_flag(sb + SM_EVT + 4);
#pragma unroll 1
    for (int job = 0; job < 2; job++) {
      const int row0 = rowb + job * 64;
      if (fast_a) {
        float sa[32], o[12];
        uint32_t pa[16], pc[16];
#pragma unroll
        for (int i = 0; i < 32; i++) sa[i] = 0.f;
#pragma unroll
        for (int i = 0; i < 12; i++) o[i] = 0.f;
        const uint64_t dk = make_desc(sb + sm_klo(0), G, 128, 0);
        mbar_wait(BAR(B_PC), 0);
        fence_regs(o);
        WG_FENCE();
        wgmma_s64(sa, q, dk);
        WG_COMMIT();
        WG_WAIT(0);
#pragma unroll 1
        for (int qi = 0; qi < 4; qi++) {
          const int qt = __shfl_sync(0xffffffff, qi, 0);
          const uint64_t dv = qt ? make_desc(sb + (19 - qt) * G, 128, qt * G + G / 2, 0) : make_desc(sb, 128, G, 0);
          const uint64_t dkq = dk + qt * 1024;
#pragma unroll
          for (int c = 0; c < 4; c++) {
            fence_regs(sa);
            exp_tile(sa, pa, cu);
            WG_FENCE();
            wgmma_s64(sa, q, dkq + c * 128 + 64);
            WG_COMMIT();
            issue_pv(o, pa, dv + c * 128);
            WG_COMMIT();
            WG_WAIT(1);
            fence_regs(sa);
            exp_tile(sa, pc, cu);
            if (c == 3 && job == 0 && qt < 3) mbar_wait(BAR(B_PC + 1 + qt), 0);
            WG_FENCE();
            wgmma_s64(sa, q, dkq + (c < 3 ? c * 128 + 128 : 1024));
            WG_COMMIT();
            issue_pv(o, pc, dv + c * 128 + 64);
            WG_COMMIT();
            if (c < 3) WG_WAIT(1); else WG_WAIT(0);
          }
          if (job && qt < 3 && lane == 0) mbar_arrive(BAR(B_Q0D + qt));
        }
        fence_regs(o);
        store_o(o, load_gate(sb, 0, row0, warp, lane), 0, h, row0, warp, lane);
      } else {
        safe_tile(sb, 0, h, row0);
        if (job) {
          asm volatile("fence.proxy.async.shared::cta;" ::: "memory");
          __syncwarp();
          if (lane < 3) mbar_arrive(BAR(B_Q0D + lane));
        }
      }
      if (job) continue;
      mbar_wait(BAR(B_PC + 4), 0);
      mbar_wait(BAR(B_OKB), 0);
      const bool fast_b = read_flag(sb + SM_EVT + 8);
#pragma unroll 1
      for (int ti = 0; ti < 2; ti++) {
        const int t = __shfl_sync(0xffffffff, wg * 2 + ti, 0);
        const int rowt = qb * 512 + t * 64;
        lds_q(q, sb + SM_QB + (t * 64 + warp * 16) * 16 + lane * 4, G);
        if (fast_b) {
          float sa[32], o[12];
          uint32_t pa[16], pc[16];
#pragma unroll
          for (int i = 0; i < 32; i++) sa[i] = 0.f;
#pragma unroll
          for (int i = 0; i < 12; i++) o[i] = 0.f;
          const uint64_t dk = make_desc(sb + SM_KB + t * 1024, 12288, 128, 0), dv = make_desc(sb + SM_VBLO + t * 1024, 128, SM_ONE1 - SM_VBLO, 0);
          const uint64_t dz = make_desc(sb + SM_VBLO, 128, 1024, 0);
          fence_regs(o);
          WG_FENCE();
          wgmma_s64(sa, q, dk);
          WG_COMMIT();
          WG_WAIT(0);
#define B_STEP(EXP, P, C)                                             \
          fence_regs(sa);                                             \
          EXP;                                                        \
          WG_FENCE();                                                 \
          wgmma_s64(sa, q, dk + 64 * ((C) + 1));                      \
          WG_COMMIT();                                                \
          issue_pv(o, P, t + (C) < cmin ? dz : dv + 64 * (C));        \
          WG_COMMIT();                                                \
          WG_WAIT(1);
          B_STEP(exp_edge<true>(sa, pa, cu, warp, lane), pa, 0)
          B_STEP(exp_tile(sa, pc, cu), pc, 1)
          B_STEP(exp_tile(sa, pa, cu), pa, 2)
          B_STEP(exp_tile(sa, pc, cu), pc, 3)
#undef B_STEP
          fence_regs(sa);
          exp_edge<false>(sa, pa, cu, warp, lane);
          WG_FENCE();
          issue_pv(o, pa, dv + 256);
          WG_COMMIT();
          const float2 g = load_gate(sb, 1, rowt, warp, lane);
          WG_WAIT(0);
          fence_regs(o);
          store_o(o, g, 1, h, rowt, warp, lane);
        } else {
          safe_tile(sb, 1, h, rowt);
        }
      }
      lds_q(q, sb + SM_QA1 + wid * 256 + lane * 4, QA1_HI);
      fence_regs(q);
      uint32_t* dst = reinterpret_cast<uint32_t*>(&g_o[(rowb >> 6) + 1][h][warp * 2][0][0]) + lane;
#pragma unroll
      for (int i = 0; i < 4; i++) st_relaxed(dst + 32 * i, EMPTY);
      __syncwarp();
      if (lane == 0) mbar_arrive(BAR(B_LAST));
    }
    __syncwarp();
    if (lane == 0) mbar_arrive(BAR(B_DONE));
    wg_sync(wg);
    if ((tid & 127) == 32) mbar_arrive_cluster(BAR(B_PEER), rank ^ 1);
  }
  if (wg < 2) {
    mbar_wait(BAR(B_EARLY), 0);
    const uint4* src = &g_o[mblk3 * 2 + 1][rank * 16 + wg * 8][0][0][0] + (tid & 127);
    uint4 v[8];
    const uint32_t t0 = clock();
    int todo = 3;
#pragma unroll
    for (int i = 0; i < 8; i++) v[i].x = EMPTY;
    do {
#pragma unroll
      for (int i = 0; i < 8; i++)
        if (v[i].x == EMPTY || v[i].y == EMPTY || v[i].z == EMPTY || v[i].w == EMPTY)
          asm volatile("ld.relaxed.gpu.global.v4.u32 {%0,%1,%2,%3}, [%4];" : "=r"(v[i].x), "=r"(v[i].y), "=r"(v[i].z), "=r"(v[i].w) : "l"(src + i * 128) : "memory");
      const bool late = (uint32_t)clock() - t0 >= WAIT_LIMIT;
#pragma unroll
      for (int b = 0; b < 2; b++) {
        bool miss = false;
#pragma unroll
        for (int i = 4 * b; i < 4 * b + 4; i++) miss |= v[i].x == EMPTY || v[i].y == EMPTY || v[i].z == EMPTY || v[i].w == EMPTY;
        if (((todo >> b) & 1) && !__any_sync(0xffffffff, miss && !late)) {
          mbar_wait(BAR(B_FREE), 0);
          const uint32_t slot = wg ? a_slot(5 + 2 * b) : a_slot(1 + 2 * b);
#pragma unroll
          for (int i = 0; i < 4; i++)
            asm volatile("st.shared.v4.u32 [%0], {%1,%2,%3,%4};" ::"r"(sb + slot + (i * 128 + (tid & 127)) * 16), "r"(v[4 * b + i].x), "r"(v[4 * b + i].y),
                         "r"(v[4 * b + i].z), "r"(v[4 * b + i].w) : "memory");
          asm volatile("fence.proxy.async.shared::cta;" ::: "memory");
          __syncwarp();
          if (lane == 0) mbar_arrive(BAR(B_LATE + wg * 2 + b));
          todo &= ~(1 << b);
        }
      }
    } while (todo);
    return;
  }

  {
    const int tile = wg & 1, w8 = wid & 7;
    const uint32_t sbd = (sb & 0x3FFFF) >> 4;
    float acc[64];
    mbar_wait(BAR(B_WO), 0);
#pragma unroll
    for (int i = 0; i < 8; i++) {
      const int s = i & 3;
      if (i == 4 && tile) {
        WG_WAIT(0);
        if (lane == 0) mbar_arrive(BAR(B_FREE));
      }
      if (i >= 4 && tile) mbar_wait(BAR(B_LATE + s), 0);
      else mbar_wait(BAR(B_AF + 2 * s) + tile * 8, i >> 2);
      const uint64_t da = (tile ? make_desc(a_slot(2 * s + 1), 128, 256, 0) : make_desc(a_slot(2 * s), 128, 256, 0)) + sbd;
      const uint64_t db = make_desc(wo_slot(2 * i), wo_slot(2 * i + 1) - wo_slot(2 * i), 1024, 1) + sbd;
      WG_FENCE();
#pragma unroll
      for (int k = 0; k < 4; k++) wgmma_n128(acc, da + k * 128, db + k * 128, (i | k) != 0);
      WG_COMMIT();
      if (i >= 1 && i <= 4 && !tile) {
        WG_WAIT(1);
        wg_sync(wg);
        if ((tid & 127) == 64) {
          if (i == 1) asm volatile("fence.proxy.async.global;" ::: "memory");
          mbar_expect(BAR(B_AF + 2 * (i - 1)), G);
          bulk_load(sb + a_slot(2 * (i - 1)), &g_o[mblk3 * 2][rank * 16 + (i - 1) * 4][0][0][0], G, BAR(B_AF + 2 * (i - 1)));
        }
      }
    }
    WG_WAIT(0);
    fence_regs(acc);
    mbar_wait_cluster(BAR(B_PEER), 0);
    const int xs = ((0x17141310 >> ((w8 >> 1) * 8)) & 0xFF) * G;
    static_assert(x_slot(0) == 0x10 * G && x_slot(1) == 0x13 * G && x_slot(2) == 0x14 * G && x_slot(3) == 0x17 * G, "");
    const uint32_t wbuf = sb + xs + (w8 & 1) * 4096;
    uint32_t peer, pbar;
    asm("mapa.shared::cluster.u32 %0, %1, %2;" : "=r"(peer) : "r"(wbuf + lane * 16), "r"(rank ^ 1));
    asm("mapa.shared::cluster.u32 %0, %1, %2;" : "=r"(pbar) : "r"(BAR(B_XCH + w8)), "r"(rank ^ 1));
#pragma unroll
    for (int i = 0; i < 8; i++)
      asm volatile("st.async.shared::cluster.mbarrier::complete_tx::bytes.v4.f32 [%0], {%1,%2,%3,%4}, [%5];" ::"r"(peer + i * 512), "f"(acc[32 + 4 * i]),
                   "f"(acc[33 + 4 * i]), "f"(acc[34 + 4 * i]), "f"(acc[35 + 4 * i]), "r"(pbar) : "memory");
    mbar_wait_cluster(BAR(B_XCH + w8), 0);
    uint32_t pk[16];
#pragma unroll
    for (int i = 0; i < 8; i++) {
      float r0, r1, r2, r3;
      asm volatile("ld.shared.v4.f32 {%0,%1,%2,%3}, [%4];" : "=f"(r0), "=f"(r1), "=f"(r2), "=f"(r3) : "r"(wbuf + lane * 16 + i * 512));
      pk[2 * i] = pack_bf16(r0 + acc[4 * i], r1 + acc[4 * i + 1]);
      pk[2 * i + 1] = pack_bf16(r2 + acc[4 * i + 2], r3 + acc[4 * i + 3]);
    }
    __syncwarp();
#pragma unroll
    for (int i = 0; i < 4; i++) {
      const int r = (lane & 7) + ((lane >> 3) & 1) * 8, chunk = 2 * i + (lane >> 4);
      asm volatile("stmatrix.sync.aligned.m8n8.x4.shared.b16 [%0], {%1,%2,%3,%4};" ::"r"(wbuf + r * 128 + ((chunk ^ (r & 7)) << 4)),
                   "r"(pk[4 * i]), "r"(pk[4 * i + 1]), "r"(pk[4 * i + 2]), "r"(pk[4 * i + 3]) : "memory");
    }
    __syncwarp();
    __nv_bfloat16* op = out + (size_t)(mblk3 * 128 + w8 * 16) * D_ + nblk * 128 + rank * 64;
#pragma unroll
    for (int i = 0; i < 4; i++) {
      const int r = i * 4 + (lane >> 3), chunk = lane & 7;
      uint4 v;
      asm volatile("ld.shared.v4.u32 {%0,%1,%2,%3}, [%4];" : "=r"(v.x), "=r"(v.y), "=r"(v.z), "=r"(v.w) : "r"(wbuf + r * 128 + ((chunk ^ (r & 7)) << 4)));
      *reinterpret_cast<uint4*>(op + r * D_ + chunk * 8) = v;
    }
  }
#undef BAR
}

__device__ float g_fq[2][S_][1536], g_fo[2][S_][D_];
__global__ void plain_qkv(const __nv_bfloat16* x, const __nv_bfloat16* wa, const __nv_bfloat16* wb) {
  const int col = blockIdx.x * 128 + threadIdx.x, row = blockIdx.y, br = blockIdx.z;
  const __nv_bfloat16* w = br ? wb : wa;
  float acc = 0.f;
  for (int k = 0; k < D_; k++) acc += __bfloat162float(x[row * D_ + k]) * __bfloat162float(w[k * 1536 + col]);
  g_fq[br][row][col] = __bfloat162float(__float2bfloat16(acc));
}
__global__ void plain_attn() {
  const int row = blockIdx.x * 64 + threadIdx.x, h = blockIdx.y, br = blockIdx.z;
  float q[16], acc[16], m = __int_as_float(0xFF800000), l = 0.f;
  for (int d = 0; d < 16; d++) { q[d] = g_fq[br][row][h * 16 + d] * 0.25f; acc[d] = 0.f; }
  for (int j = br ? max(0, row - 255) : 0; j < (br ? row + 1 : S_); j++) {
    float s = 0.f;
    for (int d = 0; d < 16; d++) s += q[d] * g_fq[br][j][512 + h * 16 + d];
    const float mn = fmaxf(m, s), r = __expf(m - mn), p = __expf(s - mn);
    l = l * r + p; m = mn;
    for (int d = 0; d < 16; d++) acc[d] = acc[d] * r + p * g_fq[br][j][1024 + h * 16 + d];
  }
  for (int d = 0; d < 16; d++) g_fo[br][row][h * 16 + d] = acc[d] / l;
}
__global__ void plain_out(const __nv_bfloat16* x, const __nv_bfloat16* gw, const __nv_bfloat16* woa, const __nv_bfloat16* wob, __nv_bfloat16* out) {
  const int col = blockIdx.x * 128 + threadIdx.x, row = blockIdx.y;
  float s = 0.f, a = 0.f, b = 0.f;
  for (int k = 0; k < D_; k++) {
    s += __bfloat162float(x[row * D_ + k]) * __bfloat162float(gw[k]);
    a += g_fo[0][row][k] * __bfloat162float(woa[k * D_ + col]);
    b += g_fo[1][row][k] * __bfloat162float(wob[k * D_ + col]);
  }
  const float g = 1.0f / (1.0f + __expf(-s));
  out[row * D_ + col] = __float2bfloat16(g * a + (1.0f - g) * b);
}
}

#define FORCE_PLAIN 0
typedef CUresult (*EncodeFn)(CUtensorMap*, CUtensorMapDataType, cuuint32_t, void*, const cuuint64_t*, const cuuint64_t*, const cuuint32_t*,
                             const cuuint32_t*, CUtensorMapInterleave, CUtensorMapSwizzle, CUtensorMapL2promotion, CUtensorMapFloatOOBfill);
static void make_map(EncodeFn fn, CUtensorMap* m, const void* p, int rows, int cols, int box_rows) {
  cuuint64_t dims[2] = {(cuuint64_t)cols, (cuuint64_t)rows};
  cuuint64_t strides[1] = {(cuuint64_t)cols * 2};
  cuuint32_t box[2] = {64, (cuuint32_t)box_rows}, es[2] = {1, 1};
  fn(m, CU_TENSOR_MAP_DATA_TYPE_BFLOAT16, 2, const_cast<void*>(p), dims, strides, box, es, CU_TENSOR_MAP_INTERLEAVE_NONE,
     CU_TENSOR_MAP_SWIZZLE_128B, CU_TENSOR_MAP_L2_PROMOTION_L2_256B, CU_TENSOR_MAP_FLOAT_OOB_FILL_NONE);
}

extern "C" void kernel_launch(void* const* d_in, const int* in_sizes, int n_in, void* d_out, int out_size) {
  const __nv_bfloat16* x = (const __nv_bfloat16*)d_in[0];
  const __nv_bfloat16* gw = (const __nv_bfloat16*)d_in[6];
  void* fp = nullptr;
  cudaDriverEntryPointQueryResult qr;
  cudaGetDriverEntryPoint("cuTensorMapEncodeTiled", &fp, cudaEnableDefault, &qr);
  EncodeFn enc = (EncodeFn)fp;
  CUtensorMap tx, twa, twb, toa, tob;
  make_map(enc, &tx, x, S_, D_, 128);
  make_map(enc, &twa, d_in[1], D_, 1536, 64);
  make_map(enc, &twb, d_in[4], D_, 1536, 64);
  make_map(enc, &toa, d_in[2], D_, D_, 64);
  make_map(enc, &tob, d_in[5], D_, D_, 64);
  CUtensorMap tst;
  {
    void* qkv = nullptr;
    cudaGetSymbolAddress(&qkv, g_qkv);
    cuuint64_t dims[2] = {(cuuint64_t)S_ * 4, 384}, strides[1] = {(cuuint64_t)S_ * 16};
    cuuint32_t box[2] = {256, 8}, es[2] = {1, 1};
    enc(&tst, CU_TENSOR_MAP_DATA_TYPE_UINT32, 2, qkv, dims, strides, box, es, CU_TENSOR_MAP_INTERLEAVE_NONE, CU_TENSOR_MAP_SWIZZLE_NONE,
        CU_TENSOR_MAP_L2_PROMOTION_NONE, CU_TENSOR_MAP_FLOAT_OOB_FILL_NONE);
  }
  cudaFuncSetAttribute(fused_kernel, cudaFuncAttributeMaxDynamicSharedMemorySize, SM_TOTAL);
  cudaLaunchConfig_t cfg = {};
  cfg.gridDim = dim3(128); cfg.blockDim = dim3(640); cfg.dynamicSmemBytes = SM_TOTAL;
  int clusters = 0;
  if (cudaOccupancyMaxActiveClusters(&clusters, fused_kernel, &cfg) != cudaSuccess || clusters < 64 || FORCE_PLAIN) {
    (void)cudaGetLastError();
    typedef const __nv_bfloat16* P;
    plain_qkv<<<dim3(12, S_, 2), 128, 0, cudaStreamPerThread>>>(x, (P)d_in[1], (P)d_in[4]);
    plain_attn<<<dim3(32, 32, 2), 64, 0, cudaStreamPerThread>>>();
    plain_out<<<dim3(4, S_), 128, 0, cudaStreamPerThread>>>(x, gw, (P)d_in[2], (P)d_in[5], (__nv_bfloat16*)d_out);
    return;
  }
  fused_kernel<<<128, 640, SM_TOTAL, cudaStreamPerThread>>>(tx, twa, twb, toa, tob, tst, gw, (__nv_bfloat16*)d_out, 1);
}
```
